```python
import torch

def _softmax(x, axis=-1):
    return torch.softmax(x, dim=axis)
def _gelu(x):
    return torch.nn.functional.gelu(x, approximate="tanh")
def _silu(x):
    return torch.nn.functional.silu(x)
def _sigmoid(x):
    return torch.sigmoid(x)
def _layernorm(x, axis=-1, eps=1e-5):
    m = x.mean(dim=axis, keepdim=True)
    v = x.var(dim=axis, keepdim=True, unbiased=False)
    return (x - m) / torch.sqrt(v + eps)
def _scatter_add(tgt, idx, src, axis=0):
    return tgt.clone().index_add_(axis, idx, src)
def _segment_sum(src, seg, n):
    out = torch.zeros((n,) + src.shape[1:], dtype=src.dtype)
    return out.index_add_(0, seg, src)
def _pad(x, pw):
    flat = tuple(v for pair in reversed(pw) for v in pair)
    return torch.nn.functional.pad(x, flat)

kernel_name = 'sequential_preLN__linear_kernel_hedgehog__mixer_token_mlp__prompt'

def setup_inputs():

    _w = (lambda a: (lambda t: t.to(torch.bfloat16) if t.is_floating_point() else t)(torch.as_tensor(a)))
    def _A_setup():
        B, S, D, H = 1, 2048, 576, 32
        Dh = D // H
        return {
            "x": _w((lambda *s: torch.randn(*s, dtype=torch.bfloat16) * 0.05)(B, S, D)),
            "wqkv": _w((lambda *s: torch.randn(*s, dtype=torch.bfloat16) * 0.2)(D, 3 * D)),
            "w_phi": _w((lambda *s: torch.randn(*s, dtype=torch.bfloat16) * 0.2)(H, Dh, Dh) * (Dh ** -0.5)),
            "wo": _w((lambda *s: torch.randn(*s, dtype=torch.bfloat16) * 0.05)(D, D)),
        }
    _A_in = _A_setup()

    def _B_setup():
        B, S, D, F = 1, 2048, 576, 4608
        return {
            "x": _w((lambda *s: torch.randn(*s, dtype=torch.bfloat16) * 0.05)(B, S, D)),
            "w1": _w((lambda *s: torch.randn(*s, dtype=torch.bfloat16) * 0.4)(S, F) * (S ** -0.5)),
            "b1": _w((lambda *s: torch.randn(*s, dtype=torch.bfloat16) * 12.8)(F) * 0.02),
            "w2": _w((lambda *s: torch.randn(*s, dtype=torch.bfloat16) * 0.4)(F, S) * (F ** -0.5)),
            "b2": _w((lambda *s: torch.randn(*s, dtype=torch.bfloat16) * 6.4)(S) * 0.02),
        }
    _B_in = _B_setup()

    return {
        "A_x": _A_in["x"],
        "A_wqkv": _A_in["wqkv"],
        "A_w_phi": _A_in["w_phi"],
        "A_wo": _A_in["wo"],
        "B_x": _B_in["x"],
        "B_w1": _B_in["w1"],
        "B_b1": _B_in["b1"],
        "B_w2": _B_in["w2"],
        "B_b2": _B_in["b2"],
    }

def reference(A_x, A_wqkv, A_w_phi, A_wo, B_x, B_w1, B_b1, B_w2, B_b2):
    def _A_ref(x, wqkv, w_phi, wo):
        B, S, D = x.shape
        H = 32; Dh = D // H
        qkv = (lambda x, *d: x.permute(*d))((x @ wqkv).reshape(B, S, 3, H, Dh), 2, 0, 3, 1, 4)
        q, k, v = qkv[0], qkv[1], qkv[2]
        pq = torch.einsum("bhsd,hdf->bhsf", q, w_phi)
        pk = torch.einsum("bhsd,hdf->bhsf", k, w_phi)
        phi_q = torch.concatenate([_softmax(pq, axis=-1), _softmax(-pq, axis=-1)], axis=-1)
        phi_k = torch.concatenate([_softmax(pk, axis=-1), _softmax(-pk, axis=-1)], axis=-1)
        kv = torch.einsum("bhsf,bhsd->bhfd", phi_k, v)
        z  = torch.einsum("bhsf->bhf", phi_k)
        num = torch.einsum("bhqf,bhfd->bhqd", phi_q, kv)
        den = torch.einsum("bhqf,bhf->bhq", phi_q, z)[..., None] + 1e-6
        o = num / den
        return (lambda x, *d: x.permute(*d))(o, 0, 2, 1, 3).reshape(B, S, D) @ wo

    def _B_ref(x, w1, b1, w2, b2):
        B, S, D = x.shape
        h = _layernorm(x, axis=-1)
        u = torch.einsum("bsd,sf->bdf", h, w1) + b1
        u = _gelu(u)
        y = torch.einsum("bdf,fs->bds", u, w2) + b2
        return (lambda x, *d: x.permute(*d))(y, 0, 2, 1)

    x = A_x
    h = x + _A_ref(_layernorm(x, axis=-1), A_wqkv, A_w_phi, A_wo)
    h2 = h + _B_ref(_layernorm(h, axis=-1), B_w1, B_b1, B_w2, B_b2)
    return h2
```

```cpp
#include <cuda_runtime.h>
#include <cuda_bf16.h>
#include <cuda.h>
#include <stdint.h>

template <int TA, int TB, int O, int T> __device__ __forceinline__ void wgmma_ss_n24(float (&d)[T], uint64_t da, uint64_t db, int sc) {
  asm volatile("{\n.reg .pred p;\nsetp.ne.b32 p, %14, 0;\n"
    "wgmma.mma_async.sync.aligned.m64n24k16.f32.bf16.bf16 {%0, %1, %2, %3, %4, %5, %6, %7, %8, %9, %10, %11}, %12, %13, p, 1, 1, %15, %16;\n}\n"
    : "+f"(d[O + 0]), "+f"(d[O + 1]), "+f"(d[O + 2]), "+f"(d[O + 3]), "+f"(d[O + 4]), "+f"(d[O + 5]), "+f"(d[O + 6]), "+f"(d[O + 7]), "+f"(d[O + 8]), "+f"(d[O + 9]), "+f"(d[O + 10]), "+f"(d[O + 11])
    : "l"(da), "l"(db), "r"(sc), "n"(TA), "n"(TB));
}
template <int TA, int TB, int O, int T> __device__ __forceinline__ void wgmma_ss_n72(float (&d)[T], uint64_t da, uint64_t db, int sc) {
  asm volatile("{\n.reg .pred p;\nsetp.ne.b32 p, %38, 0;\n"
    "wgmma.mma_async.sync.aligned.m64n72k16.f32.bf16.bf16 {%0, %1, %2, %3, %4, %5, %6, %7, %8, %9, %10, %11, %12, %13, %14, %15, %16, %17, %18, %19, %20, %21, %22, %23, %24, %25, %26, %27, %28, %29, %30, %31, %32, %33, %34, %35}, %36, %37, p, 1, 1, %39, %40;\n}\n"
    : "+f"(d[O + 0]), "+f"(d[O + 1]), "+f"(d[O + 2]), "+f"(d[O + 3]), "+f"(d[O + 4]), "+f"(d[O + 5]), "+f"(d[O + 6]), "+f"(d[O + 7]), "+f"(d[O + 8]), "+f"(d[O + 9]), "+f"(d[O + 10]), "+f"(d[O + 11]), "+f"(d[O + 12]), "+f"(d[O + 13]), "+f"(d[O + 14]), "+f"(d[O + 15]), "+f"(d[O + 16]), "+f"(d[O + 17]), "+f"(d[O + 18]), "+f"(d[O + 19]), "+f"(d[O + 20]), "+f"(d[O + 21]), "+f"(d[O + 22]), "+f"(d[O + 23]), "+f"(d[O + 24]), "+f"(d[O + 25]), "+f"(d[O + 26]), "+f"(d[O + 27]), "+f"(d[O + 28]), "+f"(d[O + 29]), "+f"(d[O + 30]), "+f"(d[O + 31]), "+f"(d[O + 32]), "+f"(d[O + 33]), "+f"(d[O + 34]), "+f"(d[O + 35])
    : "l"(da), "l"(db), "r"(sc), "n"(TA), "n"(TB));
}
template <int TA, int TB, int O, int T> __device__ __forceinline__ void wgmma_ss_n80(float (&d)[T], uint64_t da, uint64_t db, int sc) {
  asm volatile("{\n.reg .pred p;\nsetp.ne.b32 p, %42, 0;\n"
    "wgmma.mma_async.sync.aligned.m64n80k16.f32.bf16.bf16 {%0, %1, %2, %3, %4, %5, %6, %7, %8, %9, %10, %11, %12, %13, %14, %15, %16, %17, %18, %19, %20, %21, %22, %23, %24, %25, %26, %27, %28, %29, %30, %31, %32, %33, %34, %35, %36, %37, %38, %39}, %40, %41, p, 1, 1, %43, %44;\n}\n"
    : "+f"(d[O + 0]), "+f"(d[O + 1]), "+f"(d[O + 2]), "+f"(d[O + 3]), "+f"(d[O + 4]), "+f"(d[O + 5]), "+f"(d[O + 6]), "+f"(d[O + 7]), "+f"(d[O + 8]), "+f"(d[O + 9]), "+f"(d[O + 10]), "+f"(d[O + 11]), "+f"(d[O + 12]), "+f"(d[O + 13]), "+f"(d[O + 14]), "+f"(d[O + 15]), "+f"(d[O + 16]), "+f"(d[O + 17]), "+f"(d[O + 18]), "+f"(d[O + 19]), "+f"(d[O + 20]), "+f"(d[O + 21]), "+f"(d[O + 22]), "+f"(d[O + 23]), "+f"(d[O + 24]), "+f"(d[O + 25]), "+f"(d[O + 26]), "+f"(d[O + 27]), "+f"(d[O + 28]), "+f"(d[O + 29]), "+f"(d[O + 30]), "+f"(d[O + 31]), "+f"(d[O + 32]), "+f"(d[O + 33]), "+f"(d[O + 34]), "+f"(d[O + 35]), "+f"(d[O + 36]), "+f"(d[O + 37]), "+f"(d[O + 38]), "+f"(d[O + 39])
    : "l"(da), "l"(db), "r"(sc), "n"(TA), "n"(TB));
}
template <int TA, int TB, int O, int T> __device__ __forceinline__ void wgmma_ss_n96(float (&d)[T], uint64_t da, uint64_t db, int sc) {
  asm volatile("{\n.reg .pred p;\nsetp.ne.b32 p, %50, 0;\n"
    "wgmma.mma_async.sync.aligned.m64n96k16.f32.bf16.bf16 {%0, %1, %2, %3, %4, %5, %6, %7, %8, %9, %10, %11, %12, %13, %14, %15, %16, %17, %18, %19, %20, %21, %22, %23, %24, %25, %26, %27, %28, %29, %30, %31, %32, %33, %34, %35, %36, %37, %38, %39, %40, %41, %42, %43, %44, %45, %46, %47}, %48, %49, p, 1, 1, %51, %52;\n}\n"
    : "+f"(d[O + 0]), "+f"(d[O + 1]), "+f"(d[O + 2]), "+f"(d[O + 3]), "+f"(d[O + 4]), "+f"(d[O + 5]), "+f"(d[O + 6]), "+f"(d[O + 7]), "+f"(d[O + 8]), "+f"(d[O + 9]), "+f"(d[O + 10]), "+f"(d[O + 11]), "+f"(d[O + 12]), "+f"(d[O + 13]), "+f"(d[O + 14]), "+f"(d[O + 15]), "+f"(d[O + 16]), "+f"(d[O + 17]), "+f"(d[O + 18]), "+f"(d[O + 19]), "+f"(d[O + 20]), "+f"(d[O + 21]), "+f"(d[O + 22]), "+f"(d[O + 23]), "+f"(d[O + 24]), "+f"(d[O + 25]), "+f"(d[O + 26]), "+f"(d[O + 27]), "+f"(d[O + 28]), "+f"(d[O + 29]), "+f"(d[O + 30]), "+f"(d[O + 31]), "+f"(d[O + 32]), "+f"(d[O + 33]), "+f"(d[O + 34]), "+f"(d[O + 35]), "+f"(d[O + 36]), "+f"(d[O + 37]), "+f"(d[O + 38]), "+f"(d[O + 39]), "+f"(d[O + 40]), "+f"(d[O + 41]), "+f"(d[O + 42]), "+f"(d[O + 43]), "+f"(d[O + 44]), "+f"(d[O + 45]), "+f"(d[O + 46]), "+f"(d[O + 47])
    : "l"(da), "l"(db), "r"(sc), "n"(TA), "n"(TB));
}
template <int TA, int TB, int O, int T> __device__ __forceinline__ void wgmma_ss_n144(float (&d)[T], uint64_t da, uint64_t db, int sc) {
  asm volatile("{\n.reg .pred p;\nsetp.ne.b32 p, %74, 0;\n"
    "wgmma.mma_async.sync.aligned.m64n144k16.f32.bf16.bf16 {%0, %1, %2, %3, %4, %5, %6, %7, %8, %9, %10, %11, %12, %13, %14, %15, %16, %17, %18, %19, %20, %21, %22, %23, %24, %25, %26, %27, %28, %29, %30, %31, %32, %33, %34, %35, %36, %37, %38, %39, %40, %41, %42, %43, %44, %45, %46, %47, %48, %49, %50, %51, %52, %53, %54, %55, %56, %57, %58, %59, %60, %61, %62, %63, %64, %65, %66, %67, %68, %69, %70, %71}, %72, %73, p, 1, 1, %75, %76;\n}\n"
    : "+f"(d[O + 0]), "+f"(d[O + 1]), "+f"(d[O + 2]), "+f"(d[O + 3]), "+f"(d[O + 4]), "+f"(d[O + 5]), "+f"(d[O + 6]), "+f"(d[O + 7]), "+f"(d[O + 8]), "+f"(d[O + 9]), "+f"(d[O + 10]), "+f"(d[O + 11]), "+f"(d[O + 12]), "+f"(d[O + 13]), "+f"(d[O + 14]), "+f"(d[O + 15]), "+f"(d[O + 16]), "+f"(d[O + 17]), "+f"(d[O + 18]), "+f"(d[O + 19]), "+f"(d[O + 20]), "+f"(d[O + 21]), "+f"(d[O + 22]), "+f"(d[O + 23]), "+f"(d[O + 24]), "+f"(d[O + 25]), "+f"(d[O + 26]), "+f"(d[O + 27]), "+f"(d[O + 28]), "+f"(d[O + 29]), "+f"(d[O + 30]), "+f"(d[O + 31]), "+f"(d[O + 32]), "+f"(d[O + 33]), "+f"(d[O + 34]), "+f"(d[O + 35]), "+f"(d[O + 36]), "+f"(d[O + 37]), "+f"(d[O + 38]), "+f"(d[O + 39]), "+f"(d[O + 40]), "+f"(d[O + 41]), "+f"(d[O + 42]), "+f"(d[O + 43]), "+f"(d[O + 44]), "+f"(d[O + 45]), "+f"(d[O + 46]), "+f"(d[O + 47]), "+f"(d[O + 48]), "+f"(d[O + 49]), "+f"(d[O + 50]), "+f"(d[O + 51]), "+f"(d[O + 52]), "+f"(d[O + 53]), "+f"(d[O + 54]), "+f"(d[O + 55]), "+f"(d[O + 56]), "+f"(d[O + 57]), "+f"(d[O + 58]), "+f"(d[O + 59]), "+f"(d[O + 60]), "+f"(d[O + 61]), "+f"(d[O + 62]), "+f"(d[O + 63]), "+f"(d[O + 64]), "+f"(d[O + 65]), "+f"(d[O + 66]), "+f"(d[O + 67]), "+f"(d[O + 68]), "+f"(d[O + 69]), "+f"(d[O + 70]), "+f"(d[O + 71])
    : "l"(da), "l"(db), "r"(sc), "n"(TA), "n"(TB));
}
template <int TA, int TB, int O, int T> __device__ __forceinline__ void wgmma_ss_n160(float (&d)[T], uint64_t da, uint64_t db, int sc) {
  asm volatile("{\n.reg .pred p;\nsetp.ne.b32 p, %82, 0;\n"
    "wgmma.mma_async.sync.aligned.m64n160k16.f32.bf16.bf16 {%0, %1, %2, %3, %4, %5, %6, %7, %8, %9, %10, %11, %12, %13, %14, %15, %16, %17, %18, %19, %20, %21, %22, %23, %24, %25, %26, %27, %28, %29, %30, %31, %32, %33, %34, %35, %36, %37, %38, %39, %40, %41, %42, %43, %44, %45, %46, %47, %48, %49, %50, %51, %52, %53, %54, %55, %56, %57, %58, %59, %60, %61, %62, %63, %64, %65, %66, %67, %68, %69, %70, %71, %72, %73, %74, %75, %76, %77, %78, %79}, %80, %81, p, 1, 1, %83, %84;\n}\n"
    : "+f"(d[O + 0]), "+f"(d[O + 1]), "+f"(d[O + 2]), "+f"(d[O + 3]), "+f"(d[O + 4]), "+f"(d[O + 5]), "+f"(d[O + 6]), "+f"(d[O + 7]), "+f"(d[O + 8]), "+f"(d[O + 9]), "+f"(d[O + 10]), "+f"(d[O + 11]), "+f"(d[O + 12]), "+f"(d[O + 13]), "+f"(d[O + 14]), "+f"(d[O + 15]), "+f"(d[O + 16]), "+f"(d[O + 17]), "+f"(d[O + 18]), "+f"(d[O + 19]), "+f"(d[O + 20]), "+f"(d[O + 21]), "+f"(d[O + 22]), "+f"(d[O + 23]), "+f"(d[O + 24]), "+f"(d[O + 25]), "+f"(d[O + 26]), "+f"(d[O + 27]), "+f"(d[O + 28]), "+f"(d[O + 29]), "+f"(d[O + 30]), "+f"(d[O + 31]), "+f"(d[O + 32]), "+f"(d[O + 33]), "+f"(d[O + 34]), "+f"(d[O + 35]), "+f"(d[O + 36]), "+f"(d[O + 37]), "+f"(d[O + 38]), "+f"(d[O + 39]), "+f"(d[O + 40]), "+f"(d[O + 41]), "+f"(d[O + 42]), "+f"(d[O + 43]), "+f"(d[O + 44]), "+f"(d[O + 45]), "+f"(d[O + 46]), "+f"(d[O + 47]), "+f"(d[O + 48]), "+f"(d[O + 49]), "+f"(d[O + 50]), "+f"(d[O + 51]), "+f"(d[O + 52]), "+f"(d[O + 53]), "+f"(d[O + 54]), "+f"(d[O + 55]), "+f"(d[O + 56]), "+f"(d[O + 57]), "+f"(d[O + 58]), "+f"(d[O + 59]), "+f"(d[O + 60]), "+f"(d[O + 61]), "+f"(d[O + 62]), "+f"(d[O + 63]), "+f"(d[O + 64]), "+f"(d[O + 65]), "+f"(d[O + 66]), "+f"(d[O + 67]), "+f"(d[O + 68]), "+f"(d[O + 69]), "+f"(d[O + 70]), "+f"(d[O + 71]), "+f"(d[O + 72]), "+f"(d[O + 73]), "+f"(d[O + 74]), "+f"(d[O + 75]), "+f"(d[O + 76]), "+f"(d[O + 77]), "+f"(d[O + 78]), "+f"(d[O + 79])
    : "l"(da), "l"(db), "r"(sc), "n"(TA), "n"(TB));
}
template <int TA, int TB, int O, int T> __device__ __forceinline__ void wgmma_ss_n192(float (&d)[T], uint64_t da, uint64_t db, int sc) {
  asm volatile("{\n.reg .pred p;\nsetp.ne.b32 p, %98, 0;\n"
    "wgmma.mma_async.sync.aligned.m64n192k16.f32.bf16.bf16 {%0, %1, %2, %3, %4, %5, %6, %7, %8, %9, %10, %11, %12, %13, %14, %15, %16, %17, %18, %19, %20, %21, %22, %23, %24, %25, %26, %27, %28, %29, %30, %31, %32, %33, %34, %35, %36, %37, %38, %39, %40, %41, %42, %43, %44, %45, %46, %47, %48, %49, %50, %51, %52, %53, %54, %55, %56, %57, %58, %59, %60, %61, %62, %63, %64, %65, %66, %67, %68, %69, %70, %71, %72, %73, %74, %75, %76, %77, %78, %79, %80, %81, %82, %83, %84, %85, %86, %87, %88, %89, %90, %91, %92, %93, %94, %95}, %96, %97, p, 1, 1, %99, %100;\n}\n"
    : "+f"(d[O + 0]), "+f"(d[O + 1]), "+f"(d[O + 2]), "+f"(d[O + 3]), "+f"(d[O + 4]), "+f"(d[O + 5]), "+f"(d[O + 6]), "+f"(d[O + 7]), "+f"(d[O + 8]), "+f"(d[O + 9]), "+f"(d[O + 10]), "+f"(d[O + 11]), "+f"(d[O + 12]), "+f"(d[O + 13]), "+f"(d[O + 14]), "+f"(d[O + 15]), "+f"(d[O + 16]), "+f"(d[O + 17]), "+f"(d[O + 18]), "+f"(d[O + 19]), "+f"(d[O + 20]), "+f"(d[O + 21]), "+f"(d[O + 22]), "+f"(d[O + 23]), "+f"(d[O + 24]), "+f"(d[O + 25]), "+f"(d[O + 26]), "+f"(d[O + 27]), "+f"(d[O + 28]), "+f"(d[O + 29]), "+f"(d[O + 30]), "+f"(d[O + 31]), "+f"(d[O + 32]), "+f"(d[O + 33]), "+f"(d[O + 34]), "+f"(d[O + 35]), "+f"(d[O + 36]), "+f"(d[O + 37]), "+f"(d[O + 38]), "+f"(d[O + 39]), "+f"(d[O + 40]), "+f"(d[O + 41]), "+f"(d[O + 42]), "+f"(d[O + 43]), "+f"(d[O + 44]), "+f"(d[O + 45]), "+f"(d[O + 46]), "+f"(d[O + 47]), "+f"(d[O + 48]), "+f"(d[O + 49]), "+f"(d[O + 50]), "+f"(d[O + 51]), "+f"(d[O + 52]), "+f"(d[O + 53]), "+f"(d[O + 54]), "+f"(d[O + 55]), "+f"(d[O + 56]), "+f"(d[O + 57]), "+f"(d[O + 58]), "+f"(d[O + 59]), "+f"(d[O + 60]), "+f"(d[O + 61]), "+f"(d[O + 62]), "+f"(d[O + 63]), "+f"(d[O + 64]), "+f"(d[O + 65]), "+f"(d[O + 66]), "+f"(d[O + 67]), "+f"(d[O + 68]), "+f"(d[O + 69]), "+f"(d[O + 70]), "+f"(d[O + 71]), "+f"(d[O + 72]), "+f"(d[O + 73]), "+f"(d[O + 74]), "+f"(d[O + 75]), "+f"(d[O + 76]), "+f"(d[O + 77]), "+f"(d[O + 78]), "+f"(d[O + 79]), "+f"(d[O + 80]), "+f"(d[O + 81]), "+f"(d[O + 82]), "+f"(d[O + 83]), "+f"(d[O + 84]), "+f"(d[O + 85]), "+f"(d[O + 86]), "+f"(d[O + 87]), "+f"(d[O + 88]), "+f"(d[O + 89]), "+f"(d[O + 90]), "+f"(d[O + 91]), "+f"(d[O + 92]), "+f"(d[O + 93]), "+f"(d[O + 94]), "+f"(d[O + 95])
    : "l"(da), "l"(db), "r"(sc), "n"(TA), "n"(TB));
}
template <int TB, int O, int T> __device__ __forceinline__ void wgmma_rs_n72(float (&d)[T], uint32_t a0, uint32_t a1, uint32_t a2, uint32_t a3, uint64_t db, int sc) {
  asm volatile("{\n.reg .pred p;\nsetp.ne.b32 p, %41, 0;\n"
    "wgmma.mma_async.sync.aligned.m64n72k16.f32.bf16.bf16 {%0, %1, %2, %3, %4, %5, %6, %7, %8, %9, %10, %11, %12, %13, %14, %15, %16, %17, %18, %19, %20, %21, %22, %23, %24, %25, %26, %27, %28, %29, %30, %31, %32, %33, %34, %35}, {%36, %37, %38, %39}, %40, p, 1, 1, %42;\n}\n"
    : "+f"(d[O + 0]), "+f"(d[O + 1]), "+f"(d[O + 2]), "+f"(d[O + 3]), "+f"(d[O + 4]), "+f"(d[O + 5]), "+f"(d[O + 6]), "+f"(d[O + 7]), "+f"(d[O + 8]), "+f"(d[O + 9]), "+f"(d[O + 10]), "+f"(d[O + 11]), "+f"(d[O + 12]), "+f"(d[O + 13]), "+f"(d[O + 14]), "+f"(d[O + 15]), "+f"(d[O + 16]), "+f"(d[O + 17]), "+f"(d[O + 18]), "+f"(d[O + 19]), "+f"(d[O + 20]), "+f"(d[O + 21]), "+f"(d[O + 22]), "+f"(d[O + 23]), "+f"(d[O + 24]), "+f"(d[O + 25]), "+f"(d[O + 26]), "+f"(d[O + 27]), "+f"(d[O + 28]), "+f"(d[O + 29]), "+f"(d[O + 30]), "+f"(d[O + 31]), "+f"(d[O + 32]), "+f"(d[O + 33]), "+f"(d[O + 34]), "+f"(d[O + 35])
    : "r"(a0), "r"(a1), "r"(a2), "r"(a3), "l"(db), "r"(sc), "n"(TB));
}
template <int TB, int O, int T> __device__ __forceinline__ void wgmma_rs_n80(float (&d)[T], uint32_t a0, uint32_t a1, uint32_t a2, uint32_t a3, uint64_t db, int sc) {
  asm volatile("{\n.reg .pred p;\nsetp.ne.b32 p, %45, 0;\n"
    "wgmma.mma_async.sync.aligned.m64n80k16.f32.bf16.bf16 {%0, %1, %2, %3, %4, %5, %6, %7, %8, %9, %10, %11, %12, %13, %14, %15, %16, %17, %18, %19, %20, %21, %22, %23, %24, %25, %26, %27, %28, %29, %30, %31, %32, %33, %34, %35, %36, %37, %38, %39}, {%40, %41, %42, %43}, %44, p, 1, 1, %46;\n}\n"
    : "+f"(d[O + 0]), "+f"(d[O + 1]), "+f"(d[O + 2]), "+f"(d[O + 3]), "+f"(d[O + 4]), "+f"(d[O + 5]), "+f"(d[O + 6]), "+f"(d[O + 7]), "+f"(d[O + 8]), "+f"(d[O + 9]), "+f"(d[O + 10]), "+f"(d[O + 11]), "+f"(d[O + 12]), "+f"(d[O + 13]), "+f"(d[O + 14]), "+f"(d[O + 15]), "+f"(d[O + 16]), "+f"(d[O + 17]), "+f"(d[O + 18]), "+f"(d[O + 19]), "+f"(d[O + 20]), "+f"(d[O + 21]), "+f"(d[O + 22]), "+f"(d[O + 23]), "+f"(d[O + 24]), "+f"(d[O + 25]), "+f"(d[O + 26]), "+f"(d[O + 27]), "+f"(d[O + 28]), "+f"(d[O + 29]), "+f"(d[O + 30]), "+f"(d[O + 31]), "+f"(d[O + 32]), "+f"(d[O + 33]), "+f"(d[O + 34]), "+f"(d[O + 35]), "+f"(d[O + 36]), "+f"(d[O + 37]), "+f"(d[O + 38]), "+f"(d[O + 39])
    : "r"(a0), "r"(a1), "r"(a2), "r"(a3), "l"(db), "r"(sc), "n"(TB));
}
template <int N, int TA, int TB, int O = 0, int T> __device__ __forceinline__ void wgmma_ss(float (&d)[T], uint64_t da, uint64_t db, int sc) {
  if constexpr (N == 24) wgmma_ss_n24<TA, TB, O, T>(d, da, db, sc);
  if constexpr (N == 72) wgmma_ss_n72<TA, TB, O, T>(d, da, db, sc);
  if constexpr (N == 80) wgmma_ss_n80<TA, TB, O, T>(d, da, db, sc);
  if constexpr (N == 96) wgmma_ss_n96<TA, TB, O, T>(d, da, db, sc);
  if constexpr (N == 144) wgmma_ss_n144<TA, TB, O, T>(d, da, db, sc);
  if constexpr (N == 160) wgmma_ss_n160<TA, TB, O, T>(d, da, db, sc);
  if constexpr (N == 192) wgmma_ss_n192<TA, TB, O, T>(d, da, db, sc);
}
template <int N, int TB, int O = 0, int T> __device__ __forceinline__ void wgmma_rs(float (&d)[T], uint32_t a0, uint32_t a1, uint32_t a2, uint32_t a3, uint64_t db, int sc) {
  if constexpr (N == 72) wgmma_rs_n72<TB, O, T>(d, a0, a1, a2, a3, db, sc);
  if constexpr (N == 80) wgmma_rs_n80<TB, O, T>(d, a0, a1, a2, a3, db, sc);
}

namespace {

constexpr int NTHREADS = 384;
constexpr int NCTA = 132;
#define PF1_ROWS 0
#define PF2_ROWS 0
#define SIDE_KB 1
#define PACE_KB 99

constexpr int STAGE = 36864, NST = 5;
constexpr int OFF_E = NST * STAGE;
constexpr int P1_STAGE = 16384 + 24576 + 3072;
constexpr int OFF_LNX = 176128;
constexpr int OFF_CSW = OFF_LNX + 18432;
constexpr int OFF_T = 210176;
constexpr int OFF_WS = OFF_T + 11520;
constexpr int OFF_BARS = OFF_WS + 6144;
constexpr int OFF_CS = OFF_BARS + 512;
constexpr int OFF_LN = OFF_CS + 896;
constexpr int SMEM_BYTES = OFF_LN + 1024 + 1024;
constexpr int OFF_PK = 147456, PK_CS = 2080;
constexpr int OFF_V = OFF_PK + 20 * PK_CS;
constexpr int OFF_X = 18432;
constexpr int OFF_KVS = OFF_PK;
constexpr int OFF_KVB = OFF_PK + 12288;
constexpr int OFF_OST = OFF_V;
constexpr int OFF_O = 165888;

enum { B_P1F = 0, B_P1E = 4, B_OF = 8, B_RF = 17, B_WO = 22, B_CS = 23, B_RED = 24, B_SIDE = 25, B_HST = 26, B_P3DONE = 27,
       B_RE = 28, B_P1DONE = 33, B_P2DONE = 34, B_EFREE = 35, B_P3K = 36, NBARS = 40 };

__device__ __align__(1024) uint8_t g_wo[9 * 576 * 128];
__device__ __align__(1024) uint8_t g_o[32 * 72 * 1024];
__device__ __align__(1024) uint8_t g_h[32 * 4 * 18432];
__device__ __align__(1024) uint8_t g_hnT[32 * 576 * 128];
__device__ __align__(1024) uint8_t g_u[72 * 576 * 128];
__device__ __align__(1024) float g_kv[8 * 2880];
__device__ __align__(1024) uint4 g_cs[8 * 16 * 96];
__device__ __align__(1024) uint4 g_st[32 * 4 * 64];
__device__ __align__(1024) uint4 g_ln[2048];
__device__ __align__(1024) unsigned g_cnt[64 * 32];
enum { C_CS = 0, C_KV = 8, C_O = 16, C_WO = 48, C_H = 49, C_H2 = 50, C_U = 51 };
#define STAMP(i) do {} while (0)

__device__ __forceinline__ uint32_t smem_u32(const void* p) { return (uint32_t)__cvta_generic_to_shared(p); }
__device__ __forceinline__ void mbar_init(uint32_t bar, int cnt) { asm volatile("mbarrier.init.shared::cta.b64 [%0], %1;" ::"r"(bar), "r"(cnt) : "memory"); }
__device__ __forceinline__ void mbar_expect_tx(uint32_t bar, int bytes) { asm volatile("mbarrier.arrive.expect_tx.shared::cta.b64 _, [%0], %1;" ::"r"(bar), "r"(bytes) : "memory"); }
__device__ __forceinline__ void mbar_arrive(uint32_t bar) { asm volatile("mbarrier.arrive.shared::cta.b64 _, [%0];" ::"r"(bar) : "memory"); }
__device__ __forceinline__ void mbar_arrive_remote(uint32_t a) { asm volatile("mbarrier.arrive.shared::cluster.b64 _, [%0];" ::"r"(a) : "memory"); }
__device__ __forceinline__ void mbar_wait(uint32_t bar, int parity) {
  asm volatile(
      "{\n.reg .pred p;\n.reg .u32 c;\nmov.u32 c, 0;\n"
      "LAB_WAIT:\n"
      "mbarrier.try_wait.parity.shared::cta.b64 p, [%0], %1;\n"
      "@p bra DONE;\n"
      "add.u32 c, c, 1;\nsetp.lt.u32 p, c, 2000000;\n@p bra LAB_WAIT;\ntrap;\n"
      "DONE:\n}" ::"r"(bar), "r"(parity) : "memory");
}
__device__ __forceinline__ void mbar_wait_cluster(uint32_t bar, int parity) {
  asm volatile(
      "{\n.reg .pred p;\n.reg .u32 c;\nmov.u32 c, 0;\n"
      "LAB_WAIT:\n"
      "mbarrier.try_wait.parity.acquire.cluster.shared::cta.b64 p, [%0], %1;\n"
      "@p bra DONE;\n"
      "add.u32 c, c, 1;\nsetp.lt.u32 p, c, 2000000;\n@p bra LAB_WAIT;\ntrap;\n"
      "DONE:\n}" ::"r"(bar), "r"(parity) : "memory");
}
__device__ __forceinline__ bool elect_one() {
  uint32_t pred;
  asm volatile("{\n.reg .pred p;\nelect.sync _|p, 0xffffffff;\nselp.u32 %0, 1, 0, p;\n}" : "=r"(pred));
  return pred != 0;
}
__device__ __forceinline__ void bulk_load(uint32_t dst, const void* src, int bytes, uint32_t bar) {
  asm volatile("cp.async.bulk.shared::cluster.global.mbarrier::complete_tx::bytes [%0], [%1], %2, [%3];" ::"r"(dst), "l"(src), "r"(bytes), "r"(bar) : "memory");
}
__device__ __forceinline__ void bulk_store(void* dst, uint32_t src, int bytes) {
  asm volatile("cp.async.bulk.global.shared::cta.bulk_group [%0], [%1], %2;" ::"l"(dst), "r"(src), "r"(bytes) : "memory");
}
__device__ __forceinline__ void bulk_reduce_f32(void* dst, uint32_t src, int bytes) {
  asm volatile("cp.reduce.async.bulk.global.shared::cta.bulk_group.add.f32 [%0], [%1], %2;" ::"l"(dst), "r"(src), "r"(bytes) : "memory");
}
__device__ __forceinline__ void l2_prefetch(const void* src, int bytes) {
  asm volatile("cp.async.bulk.prefetch.L2.global [%0], %1;" ::"l"(src), "r"(bytes) : "memory");
}
__device__ __forceinline__ void bulk_commit_wait() { asm volatile("cp.async.bulk.commit_group;\ncp.async.bulk.wait_group 0;" ::: "memory"); }
__device__ __forceinline__ void bulk_commit_wait_read() { asm volatile("cp.async.bulk.commit_group;\ncp.async.bulk.wait_group.read 0;" ::: "memory"); }
__device__ __forceinline__ void tma2d(uint32_t dst, const CUtensorMap* m, uint32_t bar, int c0, int c1) {
  asm volatile("cp.async.bulk.tensor.2d.shared::cluster.global.mbarrier::complete_tx::bytes [%0], [%1, {%3, %4}], [%2];" ::"r"(dst), "l"(m), "r"(bar), "r"(c0), "r"(c1) : "memory");
}
__device__ __forceinline__ void tma3d(uint32_t dst, const CUtensorMap* m, uint32_t bar, int c0, int c1, int c2) {
  asm volatile("cp.async.bulk.tensor.3d.shared::cluster.global.mbarrier::complete_tx::bytes [%0], [%1, {%3, %4, %5}], [%2];" ::"r"(dst), "l"(m), "r"(bar), "r"(c0), "r"(c1), "r"(c2) : "memory");
}
__device__ __forceinline__ void tma3d_mc(uint32_t dst, const CUtensorMap* m, uint32_t bar, int c0, int c1, int c2) {
  asm volatile("cp.async.bulk.tensor.3d.shared::cluster.global.mbarrier::complete_tx::bytes.multicast::cluster [%0], [%1, {%3, %4, %5}], [%2], %6;"
               ::"r"(dst), "l"(m), "r"(bar), "r"(c0), "r"(c1), "r"(c2), "h"((uint16_t)3) : "memory");
}
__device__ __forceinline__ void fence_async_gl() { asm volatile("fence.proxy.async.global;" ::: "memory"); }
__device__ __forceinline__ void fence_async_smem() { asm volatile("fence.proxy.async.shared::cta;" ::: "memory"); }
__device__ __forceinline__ void bar_sync(int id, int n) { asm volatile("bar.sync %0, %1;" ::"r"(id), "r"(n) : "memory"); }
__device__ __forceinline__ void bar_arrive(int id, int n) { asm volatile("bar.arrive %0, %1;" ::"r"(id), "r"(n) : "memory"); }
__device__ __forceinline__ void signal_release(int c) { asm volatile("red.release.gpu.global.add.u32 [%0], 1;" ::"l"(&g_cnt[c * 32]) : "memory"); }
__device__ __forceinline__ void signal_relaxed(int c) { asm volatile("red.relaxed.gpu.global.add.u32 [%0], 1;" ::"l"(&g_cnt[c * 32]) : "memory"); }
__device__ __forceinline__ void wait_cnt(int c, unsigned target) {
  unsigned v; int it = 0;
  do {
    asm volatile("ld.relaxed.gpu.global.u32 %0, [%1];" : "=r"(v) : "l"(&g_cnt[c * 32]) : "memory");
    if (++it > 4000000) break;
  } while ((int)(v - target) < 0);
}
__device__ __forceinline__ unsigned load_cnt(int c) {
  unsigned v; asm volatile("ld.relaxed.gpu.global.u32 %0, [%1];" : "=r"(v) : "l"(&g_cnt[c * 32]) : "memory"); return v;
}
__device__ __forceinline__ void cluster_arrive() { asm volatile("barrier.cluster.arrive.relaxed.aligned;" ::: "memory"); }
__device__ __forceinline__ void cluster_wait() { asm volatile("barrier.cluster.wait.aligned;" ::: "memory"); }
__device__ __forceinline__ void wg_fence() { asm volatile("wgmma.fence.sync.aligned;" ::: "memory"); }
__device__ __forceinline__ void wg_commit() { asm volatile("wgmma.commit_group.sync.aligned;" ::: "memory"); }
template <int N> __device__ __forceinline__ void wg_wait() { asm volatile("wgmma.wait_group.sync.aligned %0;" ::"n"(N) : "memory"); }
template <int N> __device__ __forceinline__ void zero_acc(float (&d)[N]) {
#pragma unroll
  for (int i = 0; i < N; i++) d[i] = 0.f;
}
template <int N> __device__ __forceinline__ void reg_fence(float (&d)[N]) {
#pragma unroll
  for (int i = 0; i < N; i++) asm volatile("" : "+f"(d[i])::"memory");
}
__device__ __forceinline__ uint32_t pack_bf16(float lo, float hi) {
  uint32_t r; asm("cvt.rn.bf16x2.f32 %0, %1, %2;" : "=r"(r) : "f"(hi), "f"(lo)); return r;
}
__device__ __forceinline__ float bf_lo(uint32_t v) { return __uint_as_float(v << 16); }
__device__ __forceinline__ float bf_hi(uint32_t v) { return __uint_as_float(v & 0xffff0000u); }
__device__ __forceinline__ float ex2(float x) { float y; asm("ex2.approx.ftz.f32 %0, %1;" : "=f"(y) : "f"(x)); return y; }
__device__ __forceinline__ float rcp(float x) { float y; asm("rcp.approx.ftz.f32 %0, %1;" : "=f"(y) : "f"(x)); return y; }
__device__ __forceinline__ float tanh_fast(float x) { float y; asm("tanh.approx.f32 %0, %1;" : "=f"(y) : "f"(x)); return y; }
__device__ __forceinline__ void sts128(uint32_t a, uint32_t x, uint32_t y, uint32_t z, uint32_t w) {
  asm volatile("st.shared.v4.b32 [%0], {%1, %2, %3, %4};" ::"r"(a), "r"(x), "r"(y), "r"(z), "r"(w) : "memory");
}
__device__ __forceinline__ void sts64(uint32_t a, uint32_t x, uint32_t y) { asm volatile("st.shared.v2.b32 [%0], {%1, %2};" ::"r"(a), "r"(x), "r"(y) : "memory"); }
__device__ __forceinline__ void sts32f(uint32_t a, float x) { asm volatile("st.shared.f32 [%0], %1;" ::"r"(a), "f"(x) : "memory"); }
__device__ __forceinline__ void sts16(uint32_t a, uint32_t x) { asm volatile("st.shared.b16 [%0], %1;" ::"r"(a), "h"((uint16_t)x) : "memory"); }
__device__ __forceinline__ void stsm_x4(uint32_t a, uint32_t r0, uint32_t r1, uint32_t r2, uint32_t r3) {
  asm volatile("stmatrix.sync.aligned.m8n8.x4.shared.b16 [%0], {%1, %2, %3, %4};" ::"r"(a), "r"(r0), "r"(r1), "r"(r2), "r"(r3) : "memory");
}
__device__ __forceinline__ void stsm_x2(uint32_t a, uint32_t r0, uint32_t r1) {
  asm volatile("stmatrix.sync.aligned.m8n8.x2.shared.b16 [%0], {%1, %2};" ::"r"(a), "r"(r0), "r"(r1) : "memory");
}
__device__ __forceinline__ void stsm_x4_t(uint32_t a, uint32_t r0, uint32_t r1, uint32_t r2, uint32_t r3) {
  asm volatile("stmatrix.sync.aligned.m8n8.x4.trans.shared.b16 [%0], {%1, %2, %3, %4};" ::"r"(a), "r"(r0), "r"(r1), "r"(r2), "r"(r3) : "memory");
}
__device__ __forceinline__ void stsm_x2_t(uint32_t a, uint32_t r0, uint32_t r1) {
  asm volatile("stmatrix.sync.aligned.m8n8.x2.trans.shared.b16 [%0], {%1, %2};" ::"r"(a), "r"(r0), "r"(r1) : "memory");
}
__device__ __forceinline__ void ldsm_x4(uint32_t a, uint32_t& r0, uint32_t& r1, uint32_t& r2, uint32_t& r3) {
  asm volatile("ldmatrix.sync.aligned.m8n8.x4.shared.b16 {%0, %1, %2, %3}, [%4];" : "=r"(r0), "=r"(r1), "=r"(r2), "=r"(r3) : "r"(a) : "memory");
}
__device__ __forceinline__ void ldsm_x4_t(uint32_t a, uint32_t& r0, uint32_t& r1, uint32_t& r2, uint32_t& r3) {
  asm volatile("ldmatrix.sync.aligned.m8n8.x4.trans.shared.b16 {%0, %1, %2, %3}, [%4];" : "=r"(r0), "=r"(r1), "=r"(r2), "=r"(r3) : "r"(a) : "memory");
}
__device__ __forceinline__ void mma16816(float (&c)[4], uint32_t a0, uint32_t a1, uint32_t a2, uint32_t a3, uint32_t b0, uint32_t b1) {
  asm volatile("mma.sync.aligned.m16n8k16.row.col.f32.bf16.bf16.f32 {%0, %1, %2, %3}, {%4, %5, %6, %7}, {%8, %9}, {%0, %1, %2, %3};"
               : "+f"(c[0]), "+f"(c[1]), "+f"(c[2]), "+f"(c[3]) : "r"(a0), "r"(a1), "r"(a2), "r"(a3), "r"(b0), "r"(b1));
}
__device__ __forceinline__ uint32_t mapa(uint32_t a, uint32_t cta) {
  uint32_t r; asm("mapa.shared::cluster.u32 %0, %1, %2;" : "=r"(r) : "r"(a), "r"(cta)); return r;
}
__device__ __forceinline__ void st_async_v4(uint32_t a, float x, float y, float z, float w, uint32_t bar) {
  asm volatile("st.async.weak.shared::cluster.mbarrier::complete_tx::bytes.v4.f32 [%0], {%1, %2, %3, %4}, [%5];" ::"r"(a), "f"(x), "f"(y), "f"(z), "f"(w), "r"(bar) : "memory");
}
__device__ __forceinline__ uint4 ld_relaxed_v4(const void* p) {
  uint4 v; asm volatile("ld.relaxed.gpu.global.v4.u32 {%0, %1, %2, %3}, [%4];" : "=r"(v.x), "=r"(v.y), "=r"(v.z), "=r"(v.w) : "l"(p) : "memory"); return v;
}
__device__ __forceinline__ void st_relaxed_v4(void* p, uint32_t x, uint32_t y, uint32_t z, uint32_t w) {
  asm volatile("st.relaxed.gpu.global.v4.u32 [%0], {%1, %2, %3, %4};" ::"l"(p), "r"(x), "r"(y), "r"(z), "r"(w) : "memory");
}
__device__ __forceinline__ uint32_t ldg_nc(const uint32_t* p) {
  uint32_t v; asm volatile("ld.global.nc.u32 %0, [%1];" : "=r"(v) : "l"(p)); return v;
}
__device__ __forceinline__ uint4 ldg_nc_v4(const uint4* p) {
  uint4 v; asm volatile("ld.global.nc.v4.u32 {%0, %1, %2, %3}, [%4];" : "=r"(v.x), "=r"(v.y), "=r"(v.z), "=r"(v.w) : "l"(p)); return v;
}
__device__ __forceinline__ float quad_sum(float v) { v += __shfl_xor_sync(~0u, v, 1); v += __shfl_xor_sync(~0u, v, 2); return v; }

__device__ __forceinline__ constexpr uint64_t desc_hi(int lbo, int sbo, int sw) {
  return ((uint64_t)sw << 62) | ((uint64_t)(sbo >> 4) << 32) | ((uint64_t)(lbo >> 4) << 16);
}
__device__ __forceinline__ uint64_t mkdesc(uint64_t hi, uint32_t addr) { return hi | (uint64_t)((addr & 0x3FFFF) >> 4); }
constexpr uint64_t D_SW128 = desc_hi(8192, 1024, 1);

__device__ __forceinline__ uint32_t slot(int s) { return s == NST - 1 ? 0u : (uint32_t)(s + 1) * STAGE; }

struct Params {
  const __nv_bfloat16 *x, *wqkv, *wphi, *wo, *b1, *b2, *w1, *w2;
  __nv_bfloat16* out;
};

template <int HR> __device__ __forceinline__ void featmap(const float (&p)[36], uint32_t (&o)[18]) {
  constexpr float L2E = 1.4426950408889634f;
  float mx = fmaxf(p[HR], p[HR + 1]), mn = fminf(p[HR], p[HR + 1]);
#pragma unroll
  for (int j = 1; j < 9; j++) {
    mx = fmaxf(mx, fmaxf(p[4 * j + HR], p[4 * j + HR + 1]));
    mn = fminf(mn, fminf(p[4 * j + HR], p[4 * j + HR + 1]));
  }
  float a[18], b[18], sa = 0.f, sb = 0.f;
  const float mxs = -mx * L2E, mns = mn * L2E;
#pragma unroll
  for (int i = 0; i < 18; i++) {
    float v = p[4 * (i >> 1) + HR + (i & 1)];
    a[i] = ex2(fmaf(v, L2E, mxs)); sa += a[i];
    b[i] = ex2(fmaf(v, -L2E, mns)); sb += b[i];
  }
  const float ra = rcp(sa), rb = rcp(sb);
#pragma unroll
  for (int i = 0; i < 9; i++) {
    o[i] = pack_bf16(a[2 * i] * ra, a[2 * i + 1] * ra);
    o[9 + i] = pack_bf16(b[2 * i] * rb, b[2 * i + 1] * rb);
  }
}

__device__ __forceinline__ float gelu(float u) {
  float t = tanh_fast(u * fmaf(u * u, 0.0356774081363f, 0.7978845608028654f));
  float h = 0.5f * u;
  return fmaf(h, t, h);
}

__device__ __forceinline__ constexpr int qkv_idx(int part, int j) { return j < 8 ? part * 32 + 4 * j : 96 + 4 * part; }

__global__ void __cluster_dims__(2, 1, 1) __launch_bounds__(NTHREADS, 1)
fused_kernel(const __grid_constant__ CUtensorMap mX, const __grid_constant__ CUtensorMap mWm, const __grid_constant__ CUtensorMap mWr,
             const __grid_constant__ CUtensorMap mWc, const __grid_constant__ CUtensorMap mXr,
             const __grid_constant__ CUtensorMap mW1a, const __grid_constant__ CUtensorMap mW1b,
             const __grid_constant__ CUtensorMap mW2, const Params p) {
  extern __shared__ uint8_t smem_raw[];
  const uint32_t sraw = smem_u32(smem_raw);
  const uint32_t sb = (sraw + 1023) & ~1023u;
  uint8_t* smem = smem_raw + (sb - sraw);
  const uint32_t bars = sb + OFF_BARS;
  const int warp = __shfl_sync(~0u, threadIdx.x >> 5, 0), lane = threadIdx.x & 31;
  const int rank = blockIdx.x & 1;
  int pp;
  {
    int c = blockIdx.x >> 1;
    if (c < 4) pp = 60 + c;
    else if (c < 36) pp = 4 * ((c - 4) & 7) + ((c - 4) >> 3);
    else if (c < 64) pp = 32 + 4 * ((c - 36) % 7) + (c - 36) / 7;
    else pp = c;
  }
  const int L = 2 * pp + rank;
  const bool act = L < 128;
  const int p1_r = ((L >> 3) & 3) * 4 + (L & 3), p1_g = ((L >> 5) & 3) * 2 + ((L >> 2) & 1);
  if (warp != 8) cluster_arrive();
  const int p3_b = L >> 2, p3_db = L & 3;
  const int p4_fg = L / 11, p4_j = L % 11;
  const bool p4_main = p4_j < 9;
  const int p4_fb = p4_main ? (p4_fg * 6 + (p4_j / 3) * 2) : (p4_fg * 6 + (p4_j - 9) * 3);
  const int p4_d0 = p4_main ? (p4_j % 3) * 160 : 480;
  const int p5_sb = ((pp >> 3) << 1) + ((pp >> 1) & 1), p5_db = ((pp >> 2) & 1) * 2 + (pp & 1);

  if (warp >= 8) {
    asm volatile("setmaxnreg.dec.sync.aligned.u32 104;");
    if (warp == 8) {
      const bool el = elect_one();
      if (el) {
        STAMP(0);
        asm volatile("prefetch.tensormap [%0];" ::"l"(&mX) : "memory");
        asm volatile("prefetch.tensormap [%0];" ::"l"(&mWm) : "memory");
        asm volatile("prefetch.tensormap [%0];" ::"l"(&mWr) : "memory");
#pragma unroll
        for (int i = 0; i < NBARS; i++) {
          int cnt = 1;
          if (i >= B_RE) cnt = 2;
          if (i >= B_P1E && i < B_OF) cnt = 4;
          if (i == B_CS) cnt = 96;
          mbar_init(bars + 8 * i, cnt);
        }
        mbar_expect_tx(bars + 8 * B_RED, 36864);
        asm volatile("fence.mbarrier_init.release.cluster;" ::: "memory");
        fence_async_smem();
      }
      __syncwarp();
      cluster_arrive();
      if (el && act) {
        mbar_expect_tx(bars + 8 * B_P1F, P1_STAGE);
        tma2d(sb, &mX, bars + 8 * B_P1F, 0, p1_r * 128);
      }
      __syncwarp();
      cluster_wait();
      bar_arrive(8, 288);
      bar_arrive(9, 128);
      if (el) {
        unsigned ep1 = 0;
        if (!act) ep1 = load_cnt(C_U + 1) / 132 + 1;
        if (act) {
#pragma unroll 1
          for (int kb = 0; kb < 9; kb++) {
            int s = kb & 3;
            uint32_t fb = bars + 8 * (B_P1F + s), st = sb + s * P1_STAGE;
            if (kb >= 4) mbar_wait(bars + 8 * (B_P1E + s), ((kb >> 2) - 1) & 1);
            if (kb == PACE_KB) mbar_wait(bars + 8 * B_P1F, 0);
            if (kb > 0) {
              mbar_expect_tx(fb, P1_STAGE);
              tma2d(st, &mX, fb, kb * 64, p1_r * 128);
            }
            tma3d_mc(st + 16384 + rank * 12288, &mWm, fb, p1_g * 72, kb * 64 + rank * 32, 0);
            tma3d_mc(st + 40960 + rank * 1536, &mWr, fb, p1_g * 72 + 64, kb * 64 + rank * 32, 0);
            if (kb == SIDE_KB) {
              mbar_expect_tx(bars + 8 * B_SIDE, 18432 + 15552);
              bulk_load(sb + OFF_LNX, p.x + (size_t)(p1_r * 128 + p1_g * 16) * 576, 18432, bars + 8 * B_SIDE);
              tma3d(sb + OFF_CSW, &mWc, bars + 8 * B_SIDE, p1_g * 72, p1_r * 36, 0);
            }
            if (kb == 3) { ep1 = (load_cnt(C_O + p3_b) >> 3) + 1; STAMP(30); }
          }
          if (PF1_ROWS) l2_prefetch(p.w1 + (size_t)L * PF1_ROWS * 4608, PF1_ROWS * 9216);
          wait_cnt(C_WO, ep1 * 108);
          fence_async_gl();
          mbar_wait(bars + 8 * B_P1DONE, 0);
          mbar_expect_tx(bars + 8 * B_WO, 8 * 18432);
#pragma unroll 1
          for (int kb = 0; kb < 8; kb++) bulk_load(sb + kb * 18432, g_wo + ((size_t)kb * 576 + p3_db * 144) * 128, 18432, bars + 8 * B_WO);
          mbar_wait(bars + 8 * B_P2DONE, 0);
          mbar_expect_tx(bars + 8 * (B_OF + 8), 8192 + 18432 + 18432);
          bulk_load(sb + 8 * 18432, g_wo + ((size_t)8 * 576 + p3_db * 144) * 128, 18432, bars + 8 * (B_OF + 8));
          wait_cnt(C_O + p3_b, ep1 * 8);
          fence_async_gl();
          STAMP(6);
#pragma unroll 1
          for (int kb = 0; kb < 9; kb++) {
            if (kb == 7) mbar_wait(bars + 8 * B_P3K, 0);
            if (kb < 8) mbar_expect_tx(bars + 8 * (B_OF + kb), 8192);
            bulk_load(sb + (kb < 7 ? OFF_O + kb * 8192 : (kb - 7) * 8192), g_o + (size_t)(p3_b * 9 + kb) * 8192, 8192, bars + 8 * (B_OF + kb));
          }
          tma2d(sb + OFF_X, &mXr, bars + 8 * (B_OF + 8), p3_db * 144, p3_b * 64);
        }
        const int abytes4 = p4_main ? 16384 : 24576, bbytes4 = STAGE - abytes4;
        const CUtensorMap* m4 = p4_main ? &mW1a : &mW1b;
        int s = 0, ph = 1;
#pragma unroll 1
        for (int kb = 0; kb < 32; kb++) {
          uint32_t fb = bars + 8 * (B_RF + s);
          if (kb < 3) { if (act) mbar_wait(bars + 8 * (B_P3K + 1 + kb), 0); }
          else mbar_wait(bars + 8 * (B_RE + s), ph);
          mbar_expect_tx(fb, STAGE);
          tma3d(sb + slot(s), m4, fb, 0, kb * 64, p4_fb);
          if (kb >= 3) bulk_load(sb + slot(s) + abytes4, g_hnT + ((size_t)kb * 576 + p4_d0) * 128, bbytes4, fb);
          if (kb == 16 && act && PF2_ROWS) l2_prefetch(p.w2 + ((size_t)rank * 2304 + pp * PF2_ROWS) * 2048, PF2_ROWS * 4096);
          if (kb == 2) {
            if (act) mbar_wait(bars + 8 * B_P3DONE, 0);
            wait_cnt(C_H, ep1 * 128);
            fence_async_gl();
            STAMP(8);
#pragma unroll 1
            for (int q = 0; q < 3; q++) bulk_load(sb + slot(q) + abytes4, g_hnT + ((size_t)q * 576 + p4_d0) * 128, bbytes4, bars + 8 * (B_RF + q));
          }
          if (++s == NST) { s = 0; ph ^= 1; }
        }
        if (act) {
          const int s0 = s;
          wait_cnt(C_H2, ep1 * 128);
#pragma unroll 1
          for (int kb = 0; kb < 36; kb++) {
            uint32_t fb = bars + 8 * (B_RF + s);
            int kk = rank * 36 + kb;
            mbar_wait(bars + 8 * (B_RE + s), ph);
            mbar_expect_tx(fb, 16384 + 18432);
            tma3d(sb + slot(s), &mW2, fb, 0, kk * 64, p5_sb * 2);
            if (kb >= NST) bulk_load(sb + slot(s) + 16384, g_u + ((size_t)kk * 576 + p5_db * 144) * 128, 18432, fb);
            if (kb == NST - 1) {
              wait_cnt(C_U + rank, ep1 * 132);
              fence_async_gl();
              STAMP(11);
              int q = s0;
#pragma unroll 1
              for (int i = 0; i < NST; i++) {
                bulk_load(sb + slot(q) + 16384, g_u + ((size_t)(rank * 36 + i) * 576 + p5_db * 144) * 128, 18432, bars + 8 * (B_RF + q));
                if (++q == NST) q = 0;
              }
            }
            if (++s == NST) { s = 0; ph ^= 1; }
          }
        }
      }
    } else {
      const int tid = threadIdx.x - 288, aw = warp - 9;
      bar_sync(9, 128);
      unsigned ep1 = 0;
      if (act) {
        ep1 = (load_cnt(C_KV + p1_g) >> 4) + 1;
        st_relaxed_v4(g_cs + (p1_g * 16 + p1_r) * 96 + tid, 0u, 0u, 0u, 0u);
        if (tid < 64) st_relaxed_v4(g_st + (p3_b * 4 + p3_db) * 64 + tid, 0u, 0u, 0u, 0u);
        else if (tid < 80) st_relaxed_v4(g_ln + p1_r * 128 + p1_g * 16 + tid - 64, 0u, 0u, 0u, 0u);
        uint32_t wv[7];
#pragma unroll
        for (int q = 0; q < 7; q++) { int i = tid + q * 96; wv[q] = i < 648 ? __ldg(reinterpret_cast<const uint32_t*>(p.wphi + p1_g * 1296) + i) : 0u; }
#pragma unroll
        for (int q = 0; q < 8; q++) { int i = tid + q * 96; if (i < 768) sts128(sb + OFF_T + i * 16, 0u, 0u, 0u, 0u); }
        fence_async_smem();
        bar_sync(4, 96);
        if (tid == 64) {
          const int o = p1_r < 15 ? p1_r * 192 : 0;
          if (p1_r < 15) bulk_store(g_kv + p1_g * 2880 + o, sb + OFF_WS, 768);
          asm volatile("cp.async.bulk.commit_group;" ::: "memory");
        }
#pragma unroll
        for (int q = 0; q < 7; q++) {
          int i = tid + q * 96;
          if (i < 648) {
            int c = i / 9, jn = i - c * 9, t = c / 18;
            uint32_t a = sb + OFF_T + (jn * 10 + (c >> 3)) * 128 + t * 32 + (c & 7) * 2;
            sts16(a, wv[q]); sts16(a + 16, wv[q] >> 16);
          }
        }
        mbar_wait(bars + 8 * B_SIDE, 0);
        if (tid == 0) STAMP(31);
        if (aw < 2) {
          const uint4* src = reinterpret_cast<const uint4*>(smem + OFF_LNX + (tid >> 2) * 1152) + (tid & 3);
          const int rot = (tid >> 2) & 1;
          float sm = 0.f;
#pragma unroll 6
          for (int i = 0; i < 18; i++) {
            uint4 v = src[((i + rot) % 18) * 4];
            sm += ((bf_lo(v.x) + bf_hi(v.x)) + (bf_lo(v.y) + bf_hi(v.y))) + ((bf_lo(v.z) + bf_hi(v.z)) + (bf_lo(v.w) + bf_hi(v.w)));
          }
          const float mu = quad_sum(sm) * (1.f / 576.f);
          float qa = 0.f, qb = 0.f;
#pragma unroll 6
          for (int i = 0; i < 18; i++) {
            uint4 v = src[((i + rot) % 18) * 4];
            const uint32_t w[4] = {v.x, v.y, v.z, v.w};
#pragma unroll
            for (int j = 0; j < 4; j++) { float a = bf_lo(w[j]) - mu, b = bf_hi(w[j]) - mu; qa = fmaf(a, a, qa); qb = fmaf(b, b, qb); }
          }
          qa = quad_sum(qa + qb);
          if ((tid & 3) == 0) st_relaxed_v4(g_ln + p1_r * 128 + p1_g * 16 + (tid >> 2), __float_as_uint(mu), __float_as_uint(rsqrtf(qa * (1.f / 576.f) + 1e-5f)), ep1, 0u);
        } else if (lane < 27) {
          const uint4* src = reinterpret_cast<const uint4*>(smem + OFF_CSW + (lane / 9) * 5184) + lane % 9;
          float cs[8];
#pragma unroll
          for (int i = 0; i < 8; i++) cs[i] = 0.f;
#pragma unroll 6
          for (int i = 0; i < 36; i++) {
            uint4 v = src[i * 9];
            cs[0] += bf_lo(v.x); cs[1] += bf_hi(v.x); cs[2] += bf_lo(v.y); cs[3] += bf_hi(v.y);
            cs[4] += bf_lo(v.z); cs[5] += bf_hi(v.z); cs[6] += bf_lo(v.w); cs[7] += bf_hi(v.w);
          }
          if (lane == 0) asm volatile("cp.async.bulk.wait_group 0;" ::: "memory");
          __syncwarp(0x07ffffff);
          uint4* dst = g_cs + (p1_g * 16 + p1_r) * 96 + lane;
          st_relaxed_v4(dst, __float_as_uint(cs[0]), __float_as_uint(cs[1]), __float_as_uint(cs[2]), ep1);
          st_relaxed_v4(dst + 32, __float_as_uint(cs[3]), __float_as_uint(cs[4]), __float_as_uint(cs[5]), ep1);
          st_relaxed_v4(dst + 64, __float_as_uint(cs[6]), __float_as_uint(cs[7]), 0u, ep1);
        }
        if (tid == 0) STAMP(25);
        if (lane < 27) {
          uint4 e[16];
          bool ok; int it = 0;
          do {
            ok = true;
#pragma unroll
            for (int i = 0; i < 16; i++) e[i] = ld_relaxed_v4(g_cs + (p1_g * 16 + i) * 96 + tid);
#pragma unroll
            for (int i = 0; i < 16; i++) ok = ok && e[i].w == ep1;
            if (!ok) __nanosleep(300);
          } while (!ok && ++it < 2000000);
          float c0 = 0.f, c1 = 0.f, c2 = 0.f;
#pragma unroll
          for (int i = 0; i < 16; i++) { c0 += __uint_as_float(e[i].x); c1 += __uint_as_float(e[i].y); c2 += __uint_as_float(e[i].z); }
          float* d = reinterpret_cast<float*>(smem + OFF_CS) + lane * 8 + aw * 3;
          d[0] = c0; d[1] = c1;
          if (aw < 2) d[2] = c2;
        }
        if (tid < 64) {
          uint4 e0, e1; int it = 0;
          do {
            e0 = ld_relaxed_v4(g_ln + p1_r * 128 + 2 * tid); e1 = ld_relaxed_v4(g_ln + p1_r * 128 + 2 * tid + 1);
          } while ((e0.z != ep1 || e1.z != ep1) && ++it < 2000000);
          sts128(sb + OFF_LN + tid * 16, e0.x, e0.y, e1.x, e1.y);
        }
        if (tid == 0) { *reinterpret_cast<unsigned*>(smem + OFF_CS + 864) = ep1; STAMP(1); }
        fence_async_smem();
        mbar_arrive(bars + 8 * B_CS);
      }
      if (aw == 2 && L >= 24) {
        const int task = L - 24, kb = task / 12, nc = task % 12;
        int kp = kb * 64 + 2 * lane;
        int g = kp / 72, c = kp % 72;
        int src = 72 * g + 18 * ((c >> 1) & 3) + 2 * (c >> 3);
        const uint4* r0 = reinterpret_cast<const uint4*>(p.wo + (size_t)src * 576 + nc * 48);
        uint4 a[6], b[6];
#pragma unroll
        for (int q = 0; q < 6; q++) { a[q] = __ldg(r0 + q); b[q] = __ldg(r0 + 72 + q); }
        uint8_t* dst = smem + OFF_WS + (lane & 3) * 4;
#pragma unroll
        for (int q = 0; q < 6; q++) {
          uint32_t aa[4] = {a[q].x, a[q].y, a[q].z, a[q].w}, bb[4] = {b[q].x, b[q].y, b[q].z, b[q].w};
#pragma unroll
          for (int i = 0; i < 4; i++) {
            int n = q * 8 + 2 * i;
            *reinterpret_cast<uint32_t*>(dst + n * 128 + (((lane >> 2) ^ (n & 7)) << 4)) = __byte_perm(aa[i], bb[i], 0x5410);
            *reinterpret_cast<uint32_t*>(dst + (n + 1) * 128 + (((lane >> 2) ^ ((n + 1) & 7)) << 4)) = __byte_perm(aa[i], bb[i], 0x7632);
          }
        }
        fence_async_smem();
        __syncwarp();
        if (elect_one()) {
          bulk_store(g_wo + ((size_t)kb * 576 + nc * 48) * 128, sb + OFF_WS, 6144);
          bulk_commit_wait();
          signal_relaxed(C_WO);
          STAMP(2);
        }
      }
      __syncwarp();
      if (act && aw == 1) {
        bar_sync(7, 256 + 32);
        if (elect_one()) {
          mbar_wait(bars + 8 * (B_RE + 2), 0);
          bulk_store(g_h + (size_t)(p3_b * 4 + p3_db) * 18432, sb + OFF_E + 18432, 18432);
          bulk_commit_wait();
          signal_relaxed(C_H2);
          mbar_arrive(bars + 8 * B_HST);
        }
      }
      if (act && aw == 0) {
        bar_sync(3, 256 + 32);
        if (lane == 0) {
          STAMP(14);
          bulk_reduce_f32(g_kv + p1_g * 2880, sb + OFF_KVS, 11520);
          bulk_commit_wait();
          signal_relaxed(C_KV + p1_g);
          STAMP(15);
          wait_cnt(C_KV + p1_g, ep1 * 16);
          STAMP(4);
        }
        __syncwarp();
        bar_arrive(6, 256 + 32);
      }
    }
  } else {
    asm volatile("setmaxnreg.inc.sync.aligned.u32 200;");
    const int wg = warp >> 2, wq = warp & 3, tw = threadIdx.x & 127;
    const int t4 = lane & 3, r8 = lane >> 2;
    bar_sync(8, 288);
    if (act) {
      float acc[108];
      zero_acc(acc);
#pragma unroll 1
      for (int kb = 0; kb < 9; kb++) {
        const uint32_t st = sb + (kb & 3) * P1_STAGE;
        mbar_wait(bars + 8 * (B_P1F + (kb & 3)), (kb >> 2) & 1);
        if (kb == 0 && threadIdx.x == 0) STAMP(29);
        wg_fence();
        const uint64_t da = mkdesc(D_SW128, st + wg * 8192), dm = mkdesc(desc_hi(4096, 1024, 1), st + 16384), dr = mkdesc(desc_hi(128, 512, 0), st + 40960);
#pragma unroll
        for (int k = 0; k < 4; k++) {
          wgmma_ss<192, 0, 1, 0>(acc, da + 2 * k, dm + (k >> 1) * 768 + (k & 1) * 128, 1);
          wgmma_ss<24, 0, 1, 96>(acc, da + 2 * k, dr + (k >> 1) * 96 + (k & 1) * 16, 1);
        }
        wg_commit();
        wg_wait<1>();
        if (kb > 0 && kb < 6 && tw < 2) mbar_arrive_remote(mapa(bars + 8 * (B_P1E + ((kb - 1) & 3)), tw));
      }
      wg_wait<0>();
      reg_fence(acc);
      if (threadIdx.x == 0) STAMP(3);
      if (tw == 0) mbar_arrive(bars + 8 * B_P1DONE);
      mbar_wait(bars + 8 * B_CS, 0);
      const unsigned ep1 = *reinterpret_cast<const unsigned*>(smem + OFF_CS + 864);
      const float2 ln0 = *reinterpret_cast<const float2*>(smem + OFF_LN + (wg * 64 + wq * 16 + r8) * 8);
      const float2 ln1 = *reinterpret_cast<const float2*>(smem + OFF_LN + (wg * 64 + wq * 16 + r8 + 8) * 8);
      const float mu0 = ln0.x, rs0 = ln0.y, mu1 = ln1.x, rs1 = ln1.y;
      const float2* csp = reinterpret_cast<const float2*>(smem + OFF_CS) + t4;
      const uint64_t dT = mkdesc(desc_hi(128, 1280, 0), sb + OFF_T);
      auto norm_pack = [&](int part, int j, uint32_t& lo, uint32_t& hi) {
        float2 c = csp[part * 36 + j * 4];
        int i = qkv_idx(part, j);
        lo = pack_bf16(fmaf(-mu0, c.x, acc[i]) * rs0, fmaf(-mu0, c.y, acc[i + 1]) * rs0);
        hi = pack_bf16(fmaf(-mu1, c.x, acc[i + 2]) * rs1, fmaf(-mu1, c.y, acc[i + 3]) * rs1);
      };
      float pk[36], pq[36];
      {
        uint32_t f[10][2];
#pragma unroll
        for (int j = 0; j < 9; j++) norm_pack(1, j, f[j][0], f[j][1]);
        f[9][0] = f[9][1] = 0u;
        wg_fence();
#pragma unroll
        for (int i = 0; i < 5; i++) wgmma_rs<72, 0, 0>(pk, f[2 * i][0], f[2 * i][1], f[2 * i + 1][0], f[2 * i + 1][1], dT + 16 * i, i != 0);
        wg_commit();
        bar_sync(5, 256);
        uint32_t v[9][2];
#pragma unroll
        for (int j = 0; j < 9; j++) norm_pack(2, j, v[j][0], v[j][1]);
        const uint32_t va = sb + OFF_V + (wg * 64 + wq * 16 + (lane & 15)) * 16 + (lane >> 4) * 2048;
        const uint32_t one = t4 == 0 ? 0x00003F80u : 0u;
        stsm_x4(va, v[0][0], v[0][1], v[1][0], v[1][1]);
        stsm_x4(va + 2 * 2048, v[2][0], v[2][1], v[3][0], v[3][1]);
        stsm_x4(va + 4 * 2048, v[4][0], v[4][1], one, one);
        stsm_x4(va + 6 * 2048, v[5][0], v[5][1], v[6][0], v[6][1]);
        stsm_x4(va + 8 * 2048, v[7][0], v[7][1], v[8][0], v[8][1]);
        wg_wait<0>();
        reg_fence(pk);
      }
      {
        uint32_t o[18];
        uint32_t a = sb + OFF_PK + (wg * 64 + wq * 16 + r8) * 16 + t4 * 5 * PK_CS;
        featmap<0>(pk, o);
        sts128(a, o[0], o[1], o[2], o[3]); sts128(a + PK_CS, o[4], o[5], o[6], o[7]);
        sts128(a + 2 * PK_CS, o[8], o[9], o[10], o[11]); sts128(a + 3 * PK_CS, o[12], o[13], o[14], o[15]);
        sts64(a + 4 * PK_CS, o[16], o[17]);
        a += 128;
        featmap<2>(pk, o);
        sts128(a, o[0], o[1], o[2], o[3]); sts128(a + PK_CS, o[4], o[5], o[6], o[7]);
        sts128(a + 2 * PK_CS, o[8], o[9], o[10], o[11]); sts128(a + 3 * PK_CS, o[12], o[13], o[14], o[15]);
        sts64(a + 4 * PK_CS, o[16], o[17]);
      }
      fence_async_smem();
      bar_sync(5, 256);
      if (threadIdx.x == 0) STAMP(16);
      {
        float c[40];
        wg_fence();
        const uint64_t da = mkdesc(desc_hi(128, 2048, 0), sb + OFF_V + wg * 4096), db = mkdesc(desc_hi(128, PK_CS, 0), sb + OFF_PK + wg * 10 * PK_CS);
#pragma unroll
        for (int ks = 0; ks < 8; ks++) wgmma_ss<80, 1, 1, 0>(c, da + ks * 16, db + ks * 16, ks != 0);
        wg_commit();
        wg_wait<0>();
        reg_fence(c);
        bar_sync(5, 256);
#pragma unroll
        for (int hh = 0; hh < 2; hh++) {
          const int pos = 2 * wg + 2 * wq + hh;
          const int col = (pos < 5 ? 8 * pos : 8 * pos - 8) + r8;
#pragma unroll
          for (int hl = 0; hl < 2; hl++) {
            const int head = 2 * wg + hl;
            const int d = pos == 5 ? 18 + r8 : col - 18 * head;
            if (d >= 0 && d < (pos == 5 ? 20 : 18)) {
              const uint32_t a = sb + OFF_KVS + (((d >> 1) * 18 + t4) * 16 + head * 4 + (d & 1) * 2) * 4;
#pragma unroll
              for (int i = 0; i < 5; i++)
                if (i < 4 || t4 < 2) sts64(a + i * 256, __float_as_uint(c[20 * hl + 4 * i + 2 * hh]), __float_as_uint(c[20 * hl + 4 * i + 2 * hh + 1]));
            }
          }
        }
      }
      fence_async_smem();
      bar_arrive(3, 256 + 32);
      uint32_t fq0[18], fq1[18];
      {
        uint32_t f[10][2];
#pragma unroll
        for (int j = 0; j < 9; j++) norm_pack(0, j, f[j][0], f[j][1]);
        f[9][0] = f[9][1] = 0u;
        wg_fence();
#pragma unroll
        for (int i = 0; i < 5; i++) wgmma_rs<72, 0, 0>(pq, f[2 * i][0], f[2 * i][1], f[2 * i + 1][0], f[2 * i + 1][1], dT + 16 * i, i != 0);
        wg_commit();
        wg_wait<0>();
        reg_fence(pq);
        featmap<0>(pq, fq0);
        featmap<2>(pq, fq1);
      }
      if (threadIdx.x == 0) STAMP(17);
      bar_sync(6, 256 + 32);
      {
        const float* kv = g_kv + p1_g * 2880;
        uint4 v[3];
#pragma unroll
        for (int q = 0; q < 3; q++) { int i = threadIdx.x + q * 256; if (i < 720) v[q] = ld_relaxed_v4(kv + i * 4); }
#pragma unroll
        for (int q = 0; q < 3; q++) {
          int i = threadIdx.x + q * 256;
          if (i < 720) {
            uint32_t w0 = pack_bf16(__uint_as_float(v[q].x), __uint_as_float(v[q].y)), w1 = pack_bf16(__uint_as_float(v[q].z), __uint_as_float(v[q].w));
            sts128(sb + OFF_KVB + i * 32, t4 == 0 ? w0 : 0u, t4 == 1 ? w0 : 0u, t4 == 2 ? w0 : 0u, t4 == 3 ? w0 : 0u);
            sts128(sb + OFF_KVB + i * 32 + 16, t4 == 0 ? w1 : 0u, t4 == 1 ? w1 : 0u, t4 == 2 ? w1 : 0u, t4 == 3 ? w1 : 0u);
          }
        }
      }
      fence_async_smem();
      bar_sync(5, 256);
      if (threadIdx.x == 0) STAMP(18);
      {
        float oa[40];
        wg_fence();
        const uint64_t dk = mkdesc(desc_hi(128, 18 * 128, 0), sb + OFF_KVB);
#pragma unroll
        for (int i = 0; i < 9; i++) wgmma_rs<80, 0, 0>(oa, fq0[2 * i], fq1[2 * i], fq0[2 * i + 1], fq1[2 * i + 1], dk + i * 16, i != 0);
        wg_commit();
        wg_wait<0>();
        reg_fence(oa);
        const float rd0 = rcp(oa[36] + 1e-6f), rd1 = rcp(oa[38] + 1e-6f);
        const uint32_t ob = sb + OFF_OST + wg * 9216 + (lane >> 4) * 1024 + wq * 256 + (lane & 15) * 16;
#pragma unroll
        for (int j = 0; j < 8; j += 2)
          stsm_x4(ob + j * 1024, pack_bf16(oa[4 * j] * rd0, oa[4 * j + 1] * rd0), pack_bf16(oa[4 * j + 2] * rd1, oa[4 * j + 3] * rd1),
                  pack_bf16(oa[4 * j + 4] * rd0, oa[4 * j + 5] * rd0), pack_bf16(oa[4 * j + 6] * rd1, oa[4 * j + 7] * rd1));
        stsm_x2(ob + 8192, pack_bf16(oa[32] * rd0, oa[33] * rd0), pack_bf16(oa[34] * rd1, oa[35] * rd1));
      }
      fence_async_smem();
      bar_sync(1 + wg, 128);
      if (tw == 0) {
        bulk_store(g_o + ((size_t)(p1_r * 2 + wg) * 72 + p1_g * 9) * 1024, sb + OFF_OST + wg * 9216, 9216);
        bulk_commit_wait();
        signal_relaxed(C_O + p1_r * 2 + wg);
        mbar_arrive(bars + 8 * B_P2DONE);
        if (wg == 0) STAMP(5);
      }
      float ha[36];
      zero_acc(ha);
      mbar_wait(bars + 8 * B_WO, 0);
#pragma unroll 1
      for (int kb = 0; kb < 9; kb++) {
        mbar_wait(bars + 8 * (B_OF + kb), 0);
        if (kb == 0 && threadIdx.x == 0) STAMP(19);
        wg_fence();
        const uint64_t da = mkdesc(desc_hi(1024, 128, 0), sb + (kb < 7 ? OFF_O + kb * 8192 : (kb - 7) * 8192));
        const uint64_t db = mkdesc(D_SW128, sb + kb * 18432 + wg * 9216);
#pragma unroll
        for (int k = 0; k < 4; k++) wgmma_ss<72, 0, 0, 0>(ha, da + 128 * k, db + 2 * k, 1);
        wg_commit();
        if (kb >= 2 && !(kb & 1)) { wg_wait<1>(); if (tw == 0) mbar_arrive(bars + 8 * (B_P3K - 1) + 4 * kb); }
      }
      uint32_t xr[20];
      {
        const uint32_t xa = sb + OFF_X + (wq * 16 + (lane & 15)) * 288 + (wg * 9 + (lane >> 4)) * 16;
#pragma unroll
        for (int j = 0; j < 10; j += 2) ldsm_x4(xa + j * 16, xr[2 * j], xr[2 * j + 1], xr[2 * j + 2], xr[2 * j + 3]);
      }
      wg_wait<0>();
      reg_fence(ha);
      if (threadIdx.x == 0) STAMP(20);
      uint32_t hw[18];
      float s0 = 0.f, s1 = 0.f;
#pragma unroll
      for (int j = 0; j < 9; j++) {
        hw[j] = pack_bf16(bf_lo(xr[2 * j]) + ha[4 * j], bf_hi(xr[2 * j]) + ha[4 * j + 1]);
        hw[9 + j] = pack_bf16(bf_lo(xr[2 * j + 1]) + ha[4 * j + 2], bf_hi(xr[2 * j + 1]) + ha[4 * j + 3]);
        ha[4 * j] = bf_lo(hw[j]); ha[4 * j + 1] = bf_hi(hw[j]); ha[4 * j + 2] = bf_lo(hw[9 + j]); ha[4 * j + 3] = bf_hi(hw[9 + j]);
        s0 += ha[4 * j] + ha[4 * j + 1]; s1 += ha[4 * j + 2] + ha[4 * j + 3];
      }
      const float m0 = quad_sum(s0) * (1.f / 72.f), m1 = quad_sum(s1) * (1.f / 72.f);
      float q0 = 0.f, q1 = 0.f;
#pragma unroll
      for (int j = 0; j < 9; j++) {
        float a = ha[4 * j] - m0, b = ha[4 * j + 1] - m0, c = ha[4 * j + 2] - m1, d = ha[4 * j + 3] - m1;
        q0 = fmaf(a, a, q0); q0 = fmaf(b, b, q0); q1 = fmaf(c, c, q1); q1 = fmaf(d, d, q1);
      }
      q0 = quad_sum(q0); q1 = quad_sum(q1);
      if (t4 < 2) sts64(sb + OFF_LN + (wq * 16 + r8 + t4 * 8) * 16 + wg * 8, __float_as_uint(t4 ? m1 : m0), __float_as_uint(t4 ? q1 : q0));
      bar_sync(5, 256);
      if (threadIdx.x == 0) STAMP(21);
      if (threadIdx.x < 64) {
        const float4 e = *reinterpret_cast<const float4*>(smem + OFF_LN + threadIdx.x * 16);
        const float dm = e.x - e.z;
        st_relaxed_v4(g_st + (p3_b * 4 + p3_db) * 64 + threadIdx.x, __float_as_uint(0.5f * (e.x + e.z)), __float_as_uint(e.y + e.w + 36.f * dm * dm), ep1, 0u);
      }
      {
        uint4 e; int it = 0;
        do { e = ld_relaxed_v4(g_st + p3_b * 256 + threadIdx.x); } while (e.z != ep1 && ++it < 2000000);
        sts64(sb + OFF_WS + (threadIdx.x & 63) * 32 + (threadIdx.x >> 6) * 8, e.x, e.y);
      }
      bar_sync(5, 256);
      float mean[2], scale[2];
#pragma unroll
      for (int hr = 0; hr < 2; hr++) {
        const float4* sp = reinterpret_cast<const float4*>(smem + OFF_WS + (wq * 16 + r8 + hr * 8) * 32);
        const float4 a = sp[0], b = sp[1];
        const float mu = 0.25f * ((a.x + a.z) + (b.x + b.z));
        const float d0 = a.x - mu, d1 = a.z - mu, d2 = b.x - mu, d3 = b.z - mu;
        const float var = ((a.y + a.w) + (b.y + b.w) + 144.f * (d0 * d0 + d1 * d1 + d2 * d2 + d3 * d3)) * (1.f / 576.f);
        const float r1 = rsqrtf(var + 1e-5f);
        const float var2 = var * r1 * r1;
        mean[hr] = mu; scale[hr] = r1 * rsqrtf(var2 + 1e-5f);
      }
      if (threadIdx.x == 0) STAMP(22);
      {
        const uint32_t eb = sb + OFF_E + wg * 9216 + ((lane >> 4) * 8 + (lane & 7)) * 128 + (((wq * 2 + ((lane >> 3) & 1)) ^ (lane & 7)) << 4);
#pragma unroll
        for (int j = 0; j < 8; j += 2)
          stsm_x4_t(eb + j * 1024, pack_bf16((ha[4 * j] - mean[0]) * scale[0], (ha[4 * j + 1] - mean[0]) * scale[0]),
                    pack_bf16((ha[4 * j + 2] - mean[1]) * scale[1], (ha[4 * j + 3] - mean[1]) * scale[1]),
                    pack_bf16((ha[4 * j + 4] - mean[0]) * scale[0], (ha[4 * j + 5] - mean[0]) * scale[0]),
                    pack_bf16((ha[4 * j + 6] - mean[1]) * scale[1], (ha[4 * j + 7] - mean[1]) * scale[1]));
        stsm_x2_t(eb + 8192, pack_bf16((ha[32] - mean[0]) * scale[0], (ha[33] - mean[0]) * scale[0]),
                  pack_bf16((ha[34] - mean[1]) * scale[1], (ha[35] - mean[1]) * scale[1]));
      }
      fence_async_smem();
      bar_sync(5, 256);
      if (threadIdx.x == 0) {
        STAMP(23);
        bulk_store(g_hnT + ((size_t)p3_b * 576 + p3_db * 144) * 128, sb + OFF_E, 18432);
        asm volatile("cp.async.bulk.commit_group;" ::: "memory");
        mbar_arrive(bars + 8 * B_P3DONE);
        asm volatile("cp.async.bulk.wait_group 0;" ::: "memory");
        signal_relaxed(C_H);
        STAMP(7);
      }
      {
        const uint32_t hb = sb + OFF_E + 18432 + wg * 4608;
#pragma unroll
        for (int hr = 0; hr < 2; hr++) {
          sts128(hb + hr * 9216 + tw * 16, hw[9 * hr], hw[9 * hr + 1], hw[9 * hr + 2], hw[9 * hr + 3]);
          sts128(hb + hr * 9216 + 2048 + tw * 16, hw[9 * hr + 4], hw[9 * hr + 5], hw[9 * hr + 6], hw[9 * hr + 7]);
          sts32f(hb + hr * 9216 + 4096 + tw * 4, __uint_as_float(hw[9 * hr + 8]));
        }
        fence_async_smem();
        bar_arrive(7, 256 + 32);
      }
    }
    int s = 0, ph = 0;
    {
      float acc[96];
      const int f = (p4_fb + wg) * 64 + wq * 16 + r8, f2 = (p4_fb + 2) * 64 + wq * 16 + r8;
      const float bb0 = __bfloat162float(p.b1[f]), bb1 = __bfloat162float(p.b1[f + 8]);
      float bc0 = bb0, bc1 = bb1;
      if (!p4_main) { bc0 = __bfloat162float(p.b1[f2]); bc1 = __bfloat162float(p.b1[f2 + 8]); }
      int prev = 0;
      const int mode = p4_main ? 0 : 1 + wg;
#define P4_LOOP(BODY)                                                                          \
  _Pragma("unroll 1") for (int kb = 0; kb < 32; kb++) {                                        \
    mbar_wait(bars + 8 * (B_RF + s), ph);                                                      \
    if (kb == 0 && threadIdx.x == 0) STAMP(27);                                                \
    wg_fence();                                                                                \
    const uint64_t da = mkdesc(D_SW128, sb + slot(s) + wg * 8192);                           \
    _Pragma("unroll") for (int k = 0; k < 4; k++) { BODY }                                     \
    wg_commit();                                                                               \
    if (kb > 0) { wg_wait<1>(); if (tw == 0) mbar_arrive(bars + 8 * (B_RE + prev)); }          \
    prev = s;                                                                                  \
    if (++s == NST) { s = 0; ph ^= 1; }                                                        \
  }                                                                                            \
  wg_wait<0>();
      if (mode == 0) {
        float t[80];
        zero_acc(t);
        P4_LOOP((wgmma_ss<160, 1, 0, 0>(t, da + 128 * k, mkdesc(D_SW128, sb + slot(s) + 16384) + 2 * k, 1));)
        reg_fence(t);
#pragma unroll
        for (int i = 0; i < 96; i++) acc[i] = i < 80 ? t[i] + ((i & 2) ? bb1 : bb0) : 0.f;
      } else if (mode == 1) {
        float t[48], u[48];
        zero_acc(t); zero_acc(u);
        P4_LOOP((wgmma_ss<96, 1, 0, 0>(t, da + 128 * k, mkdesc(D_SW128, sb + slot(s) + 24576) + 2 * k, 1));
                (wgmma_ss<96, 1, 0, 0>(u, da + 1024 + 128 * k, mkdesc(D_SW128, sb + slot(s) + 24576) + 2 * k, 1));)
        reg_fence(t); reg_fence(u);
#pragma unroll
        for (int i = 0; i < 48; i++) { acc[i] = t[i] + ((i & 2) ? bb1 : bb0); acc[48 + i] = u[i] + ((i & 2) ? bc1 : bc0); }
      } else {
        float t[48];
        zero_acc(t);
        P4_LOOP((wgmma_ss<96, 1, 0, 0>(t, da + 128 * k, mkdesc(D_SW128, sb + slot(s) + 24576) + 2 * k, 1));)
        reg_fence(t);
#pragma unroll
        for (int i = 0; i < 96; i++) acc[i] = i < 48 ? t[i] + ((i & 2) ? bb1 : bb0) : 0.f;
      }
      if (tw == 0) mbar_arrive(bars + 8 * (B_RE + prev));
      if (threadIdx.x == 0) STAMP(9);
      if (act) mbar_wait(bars + 8 * B_HST, 0);
      const uint32_t ebase = sb + OFF_E + wg * (p4_main ? 20480 : 24576);
      const uint32_t eb = ebase + ((lane >> 4) * 8 + (lane & 7)) * 128 + (((wq * 2 + ((lane >> 3) & 1)) ^ (lane & 7)) << 4);
      const int npair = mode == 0 ? 10 : (mode == 1 ? 12 : 6);
#pragma unroll
      for (int jj = 0; jj < 12; jj++) {
        if (jj < npair) {
          stsm_x4_t(eb + jj * 2048, pack_bf16(gelu(acc[8 * jj]), gelu(acc[8 * jj + 1])), pack_bf16(gelu(acc[8 * jj + 2]), gelu(acc[8 * jj + 3])),
                    pack_bf16(gelu(acc[8 * jj + 4]), gelu(acc[8 * jj + 5])), pack_bf16(gelu(acc[8 * jj + 6]), gelu(acc[8 * jj + 7])));
        }
      }
      fence_async_smem();
      bar_sync(1 + wg, 128);
      if (tw == 0) {
        if (wg == 0) STAMP(24);
        bulk_store(g_u + ((size_t)(p4_fb + wg) * 576 + p4_d0) * 128, ebase, p4_main ? 20480 : 12288);
        if (mode == 1) bulk_store(g_u + ((size_t)(p4_fb + 2) * 576 + 480) * 128, ebase + 12288, 12288);
        bulk_commit_wait();
        signal_relaxed(C_U + (p4_fg >= 6));
        mbar_arrive_remote(mapa(bars + 8 * B_EFREE, rank ^ 1));
        if (wg == 0) STAMP(10);
      }
    }
    if (act) {
      float acc[72];
      zero_acc(acc);
      int prev = 0;
#pragma unroll 1
      for (int kb = 0; kb < 36; kb++) {
        mbar_wait(bars + 8 * (B_RF + s), ph);
        if (kb == 0 && threadIdx.x == 0) STAMP(28);
        wg_fence();
        const uint64_t da = mkdesc(D_SW128, sb + slot(s) + wg * 8192), db = mkdesc(D_SW128, sb + slot(s) + 16384);
#pragma unroll
        for (int k = 0; k < 4; k++) wgmma_ss<144, 1, 0, 0>(acc, da + 128 * k, db + 2 * k, 1);
        wg_commit();
        if (kb > 0) { wg_wait<1>(); if (tw == 0) mbar_arrive(bars + 8 * (B_RE + prev)); }
        prev = s;
        if (++s == NST) { s = 0; ph ^= 1; }
      }
      uint4 hr[4];
      uint32_t hl[2];
      {
        const uint8_t* hp = g_h + (size_t)((p5_sb * 2 + wg) * 4 + p5_db) * 18432 + rank * 9216;
#pragma unroll
        for (int i = 0; i < 2; i++) {
          hr[2 * i] = __ldcg(reinterpret_cast<const uint4*>(hp + i * 4608) + tw);
          hr[2 * i + 1] = __ldcg(reinterpret_cast<const uint4*>(hp + i * 4608 + 2048) + tw);
          hl[i] = __ldcg(reinterpret_cast<const uint32_t*>(hp + i * 4608 + 4096) + tw);
        }
      }
      const int srow = p5_sb * 128 + wg * 64 + wq * 16 + rank * 8;
      const float bb = __bfloat162float(p.b2[srow + r8]);
      wg_wait<0>();
      reg_fence(acc);
      if (threadIdx.x == 0) STAMP(12);
      mbar_wait(bars + 8 * B_EFREE, 0);
      {
        const uint32_t dst = mapa(sb + OFF_E + threadIdx.x * 16, rank ^ 1), rb = mapa(bars + 8 * B_RED, rank ^ 1);
#pragma unroll
        for (int j = 0; j < 9; j++) {
          st_async_v4(dst + j * 4096, rank ? acc[8 * j] : acc[8 * j + 2], rank ? acc[8 * j + 1] : acc[8 * j + 3],
                      rank ? acc[8 * j + 4] : acc[8 * j + 6], rank ? acc[8 * j + 5] : acc[8 * j + 7], rb);
          if (rank) { acc[8 * j] = acc[8 * j + 2]; acc[8 * j + 1] = acc[8 * j + 3]; acc[8 * j + 4] = acc[8 * j + 6]; acc[8 * j + 5] = acc[8 * j + 7]; }
        }
      }
      const uint32_t hw[18] = {hr[0].x, hr[0].y, hr[0].z, hr[0].w, hr[1].x, hr[1].y, hr[1].z, hr[1].w, hl[0],
                               hr[2].x, hr[2].y, hr[2].z, hr[2].w, hr[3].x, hr[3].y, hr[3].z, hr[3].w, hl[1]};
      mbar_wait_cluster(bars + 8 * B_RED, 0);
      if (threadIdx.x == 0) STAMP(26);
      uint32_t ow[18];
#pragma unroll
      for (int j = 0; j < 9; j++) {
        float4 r = *reinterpret_cast<const float4*>(smem + OFF_E + j * 4096 + threadIdx.x * 16);
        ow[2 * j] = pack_bf16(bf_lo(hw[2 * j]) + (acc[8 * j] + r.x + bb), bf_hi(hw[2 * j]) + (acc[8 * j + 1] + r.y + bb));
        ow[2 * j + 1] = pack_bf16(bf_lo(hw[2 * j + 1]) + (acc[8 * j + 4] + r.z + bb), bf_hi(hw[2 * j + 1]) + (acc[8 * j + 5] + r.w + bb));
      }
      const uint32_t ob = sb + wq * STAGE + wg * 8192;
      const uint32_t oa = ob + (lane & 7) * 304 + (lane >> 3) * 16;
#pragma unroll
      for (int j = 0; j < 16; j += 4) stsm_x4(oa + j * 16, ow[j], ow[j + 1], ow[j + 2], ow[j + 3]);
      stsm_x2(oa + 256, ow[16], ow[17]);
      fence_async_smem();
      __syncwarp();
      if (lane < 8) {
        bulk_store(p.out + (size_t)(srow + lane) * 576 + p5_db * 144, ob + lane * 304, 288);
        bulk_commit_wait_read();
      }
      if (threadIdx.x == 0) STAMP(13);
    } else {
      mbar_wait(bars + 8 * B_EFREE, 0);
    }
  }
}

typedef CUresult (*EncodeFn)(CUtensorMap*, CUtensorMapDataType, cuuint32_t, void*, const cuuint64_t*, const cuuint64_t*,
                             const cuuint32_t*, const cuuint32_t*, CUtensorMapInterleave, CUtensorMapSwizzle,
                             CUtensorMapL2promotion, CUtensorMapFloatOOBfill);

CUtensorMap make_map(EncodeFn enc, const void* ptr, int rank, const cuuint64_t* dims, const cuuint64_t* strides, const cuuint32_t* box,
                     CUtensorMapSwizzle sw) {
  CUtensorMap m;
  cuuint32_t es[3] = {1, 1, 1};
  enc(&m, CU_TENSOR_MAP_DATA_TYPE_BFLOAT16, rank, const_cast<void*>(ptr), dims, strides, box, es, CU_TENSOR_MAP_INTERLEAVE_NONE,
      sw, CU_TENSOR_MAP_L2_PROMOTION_L2_256B, CU_TENSOR_MAP_FLOAT_OOB_FILL_NONE);
  return m;
}
CUtensorMap make_wmap(EncodeFn enc, const void* ptr, uint64_t rows, uint64_t cols, uint32_t nblk) {
  cuuint64_t dims[3] = {64, rows, cols / 64};
  cuuint64_t strides[2] = {cols * 2, 128};
  cuuint32_t box[3] = {64, 64, nblk};
  return make_map(enc, ptr, 3, dims, strides, box, CU_TENSOR_MAP_SWIZZLE_128B);
}

}

extern "C" void kernel_launch(void* const* d_in, const int* in_sizes, int n_in, void* d_out, int out_size) {
  static EncodeFn enc = nullptr;
  if (!enc) {
    cudaDriverEntryPointQueryResult qr;
    cudaGetDriverEntryPoint("cuTensorMapEncodeTiled", (void**)&enc, cudaEnableDefault, &qr);
    cudaFuncSetAttribute(fused_kernel, cudaFuncAttributeMaxDynamicSharedMemorySize, SMEM_BYTES);
  }
  Params p;
  p.x = (const __nv_bfloat16*)d_in[0];
  p.wqkv = (const __nv_bfloat16*)d_in[1];
  p.wphi = (const __nv_bfloat16*)d_in[2];
  p.wo = (const __nv_bfloat16*)d_in[3];
  p.b1 = (const __nv_bfloat16*)d_in[6];
  p.b2 = (const __nv_bfloat16*)d_in[8];
  p.w1 = (const __nv_bfloat16*)d_in[5];
  p.w2 = (const __nv_bfloat16*)d_in[7];
  p.out = (__nv_bfloat16*)d_out;
  CUtensorMap mX, mXr, mWm, mWr, mWc;
  {
    cuuint64_t dims[2] = {576, 2048}; cuuint64_t strides[1] = {1152}; cuuint32_t box[2] = {64, 128};
    mX = make_map(enc, d_in[0], 2, dims, strides, box, CU_TENSOR_MAP_SWIZZLE_128B);
    cuuint32_t boxr[2] = {144, 64};
    mXr = make_map(enc, d_in[0], 2, dims, strides, boxr, CU_TENSOR_MAP_SWIZZLE_NONE);
  }
  {
    cuuint64_t dims[3] = {576, 576, 3}; cuuint64_t strides[2] = {3456, 1152};
    cuuint32_t boxm[3] = {64, 32, 3}, boxr[3] = {8, 32, 3}, boxc[3] = {72, 36, 3};
    mWc = make_map(enc, d_in[1], 3, dims, strides, boxc, CU_TENSOR_MAP_SWIZZLE_NONE);
    mWm = make_map(enc, d_in[1], 3, dims, strides, boxm, CU_TENSOR_MAP_SWIZZLE_128B);
    mWr = make_map(enc, d_in[1], 3, dims, strides, boxr, CU_TENSOR_MAP_SWIZZLE_NONE);
  }
  CUtensorMap mW1a = make_wmap(enc, d_in[5], 2048, 4608, 2);
  CUtensorMap mW1b = make_wmap(enc, d_in[5], 2048, 4608, 3);
  CUtensorMap mW2 = make_wmap(enc, d_in[7], 4608, 2048, 2);
  fused_kernel<<<NCTA, NTHREADS, SMEM_BYTES, cudaStreamPerThread>>>(mX, mWm, mWr, mWc, mXr, mW1a, mW1b, mW2, p);
}
```

```cpp
#include <cuda_runtime.h>
#include <cuda_bf16.h>
#include <cuda.h>
#include <stdint.h>

template <int TA, int TB, int O, int T> __device__ __forceinline__ void wgmma_ss_n24(float (&d)[T], uint64_t da, uint64_t db, int sc) {
  asm volatile("{\n.reg .pred p;\nsetp.ne.b32 p, %14, 0;\n"
    "wgmma.mma_async.sync.aligned.m64n24k16.f32.bf16.bf16 {%0, %1, %2, %3, %4, %5, %6, %7, %8, %9, %10, %11}, %12, %13, p, 1, 1, %15, %16;\n}\n"
    : "+f"(d[O + 0]), "+f"(d[O + 1]), "+f"(d[O + 2]), "+f"(d[O + 3]), "+f"(d[O + 4]), "+f"(d[O + 5]), "+f"(d[O + 6]), "+f"(d[O + 7]), "+f"(d[O + 8]), "+f"(d[O + 9]), "+f"(d[O + 10]), "+f"(d[O + 11])
    : "l"(da), "l"(db), "r"(sc), "n"(TA), "n"(TB));
}
template <int TA, int TB, int O, int T> __device__ __forceinline__ void wgmma_ss_n72(float (&d)[T], uint64_t da, uint64_t db, int sc) {
  asm volatile("{\n.reg .pred p;\nsetp.ne.b32 p, %38, 0;\n"
    "wgmma.mma_async.sync.aligned.m64n72k16.f32.bf16.bf16 {%0, %1, %2, %3, %4, %5, %6, %7, %8, %9, %10, %11, %12, %13, %14, %15, %16, %17, %18, %19, %20, %21, %22, %23, %24, %25, %26, %27, %28, %29, %30, %31, %32, %33, %34, %35}, %36, %37, p, 1, 1, %39, %40;\n}\n"
    : "+f"(d[O + 0]), "+f"(d[O + 1]), "+f"(d[O + 2]), "+f"(d[O + 3]), "+f"(d[O + 4]), "+f"(d[O + 5]), "+f"(d[O + 6]), "+f"(d[O + 7]), "+f"(d[O + 8]), "+f"(d[O + 9]), "+f"(d[O + 10]), "+f"(d[O + 11]), "+f"(d[O + 12]), "+f"(d[O + 13]), "+f"(d[O + 14]), "+f"(d[O + 15]), "+f"(d[O + 16]), "+f"(d[O + 17]), "+f"(d[O + 18]), "+f"(d[O + 19]), "+f"(d[O + 20]), "+f"(d[O + 21]), "+f"(d[O + 22]), "+f"(d[O + 23]), "+f"(d[O + 24]), "+f"(d[O + 25]), "+f"(d[O + 26]), "+f"(d[O + 27]), "+f"(d[O + 28]), "+f"(d[O + 29]), "+f"(d[O + 30]), "+f"(d[O + 31]), "+f"(d[O + 32]), "+f"(d[O + 33]), "+f"(d[O + 34]), "+f"(d[O + 35])
    : "l"(da), "l"(db), "r"(sc), "n"(TA), "n"(TB));
}
template <int TA, int TB, int O, int T> __device__ __forceinline__ void wgmma_ss_n80(float (&d)[T], uint64_t da, uint64_t db, int sc) {
  asm volatile("{\n.reg .pred p;\nsetp.ne.b32 p, %42, 0;\n"
    "wgmma.mma_async.sync.aligned.m64n80k16.f32.bf16.bf16 {%0, %1, %2, %3, %4, %5, %6, %7, %8, %9, %10, %11, %12, %13, %14, %15, %16, %17, %18, %19, %20, %21, %22, %23, %24, %25, %26, %27, %28, %29, %30, %31, %32, %33, %34, %35, %36, %37, %38, %39}, %40, %41, p, 1, 1, %43, %44;\n}\n"
    : "+f"(d[O + 0]), "+f"(d[O + 1]), "+f"(d[O + 2]), "+f"(d[O + 3]), "+f"(d[O + 4]), "+f"(d[O + 5]), "+f"(d[O + 6]), "+f"(d[O + 7]), "+f"(d[O + 8]), "+f"(d[O + 9]), "+f"(d[O + 10]), "+f"(d[O + 11]), "+f"(d[O + 12]), "+f"(d[O + 13]), "+f"(d[O + 14]), "+f"(d[O + 15]), "+f"(d[O + 16]), "+f"(d[O + 17]), "+f"(d[O + 18]), "+f"(d[O + 19]), "+f"(d[O + 20]), "+f"(d[O + 21]), "+f"(d[O + 22]), "+f"(d[O + 23]), "+f"(d[O + 24]), "+f"(d[O + 25]), "+f"(d[O + 26]), "+f"(d[O + 27]), "+f"(d[O + 28]), "+f"(d[O + 29]), "+f"(d[O + 30]), "+f"(d[O + 31]), "+f"(d[O + 32]), "+f"(d[O + 33]), "+f"(d[O + 34]), "+f"(d[O + 35]), "+f"(d[O + 36]), "+f"(d[O + 37]), "+f"(d[O + 38]), "+f"(d[O + 39])
    : "l"(da), "l"(db), "r"(sc), "n"(TA), "n"(TB));
}
template <int TA, int TB, int O, int T> __device__ __forceinline__ void wgmma_ss_n96(float (&d)[T], uint64_t da, uint64_t db, int sc) {
  asm volatile("{\n.reg .pred p;\nsetp.ne.b32 p, %50, 0;\n"
    "wgmma.mma_async.sync.aligned.m64n96k16.f32.bf16.bf16 {%0, %1, %2, %3, %4, %5, %6, %7, %8, %9, %10, %11, %12, %13, %14, %15, %16, %17, %18, %19, %20, %21, %22, %23, %24, %25, %26, %27, %28, %29, %30, %31, %32, %33, %34, %35, %36, %37, %38, %39, %40, %41, %42, %43, %44, %45, %46, %47}, %48, %49, p, 1, 1, %51, %52;\n}\n"
    : "+f"(d[O + 0]), "+f"(d[O + 1]), "+f"(d[O + 2]), "+f"(d[O + 3]), "+f"(d[O + 4]), "+f"(d[O + 5]), "+f"(d[O + 6]), "+f"(d[O + 7]), "+f"(d[O + 8]), "+f"(d[O + 9]), "+f"(d[O + 10]), "+f"(d[O + 11]), "+f"(d[O + 12]), "+f"(d[O + 13]), "+f"(d[O + 14]), "+f"(d[O + 15]), "+f"(d[O + 16]), "+f"(d[O + 17]), "+f"(d[O + 18]), "+f"(d[O + 19]), "+f"(d[O + 20]), "+f"(d[O + 21]), "+f"(d[O + 22]), "+f"(d[O + 23]), "+f"(d[O + 24]), "+f"(d[O + 25]), "+f"(d[O + 26]), "+f"(d[O + 27]), "+f"(d[O + 28]), "+f"(d[O + 29]), "+f"(d[O + 30]), "+f"(d[O + 31]), "+f"(d[O + 32]), "+f"(d[O + 33]), "+f"(d[O + 34]), "+f"(d[O + 35]), "+f"(d[O + 36]), "+f"(d[O + 37]), "+f"(d[O + 38]), "+f"(d[O + 39]), "+f"(d[O + 40]), "+f"(d[O + 41]), "+f"(d[O + 42]), "+f"(d[O + 43]), "+f"(d[O + 44]), "+f"(d[O + 45]), "+f"(d[O + 46]), "+f"(d[O + 47])
    : "l"(da), "l"(db), "r"(sc), "n"(TA), "n"(TB));
}
template <int TA, int TB, int O, int T> __device__ __forceinline__ void wgmma_ss_n144(float (&d)[T], uint64_t da, uint64_t db, int sc) {
  asm volatile("{\n.reg .pred p;\nsetp.ne.b32 p, %74, 0;\n"
    "wgmma.mma_async.sync.aligned.m64n144k16.f32.bf16.bf16 {%0, %1, %2, %3, %4, %5, %6, %7, %8, %9, %10, %11, %12, %13, %14, %15, %16, %17, %18, %19, %20, %21, %22, %23, %24, %25, %26, %27, %28, %29, %30, %31, %32, %33, %34, %35, %36, %37, %38, %39, %40, %41, %42, %43, %44, %45, %46, %47, %48, %49, %50, %51, %52, %53, %54, %55, %56, %57, %58, %59, %60, %61, %62, %63, %64, %65, %66, %67, %68, %69, %70, %71}, %72, %73, p, 1, 1, %75, %76;\n}\n"
    : "+f"(d[O + 0]), "+f"(d[O + 1]), "+f"(d[O + 2]), "+f"(d[O + 3]), "+f"(d[O + 4]), "+f"(d[O + 5]), "+f"(d[O + 6]), "+f"(d[O + 7]), "+f"(d[O + 8]), "+f"(d[O + 9]), "+f"(d[O + 10]), "+f"(d[O + 11]), "+f"(d[O + 12]), "+f"(d[O + 13]), "+f"(d[O + 14]), "+f"(d[O + 15]), "+f"(d[O + 16]), "+f"(d[O + 17]), "+f"(d[O + 18]), "+f"(d[O + 19]), "+f"(d[O + 20]), "+f"(d[O + 21]), "+f"(d[O + 22]), "+f"(d[O + 23]), "+f"(d[O + 24]), "+f"(d[O + 25]), "+f"(d[O + 26]), "+f"(d[O + 27]), "+f"(d[O + 28]), "+f"(d[O + 29]), "+f"(d[O + 30]), "+f"(d[O + 31]), "+f"(d[O + 32]), "+f"(d[O + 33]), "+f"(d[O + 34]), "+f"(d[O + 35]), "+f"(d[O + 36]), "+f"(d[O + 37]), "+f"(d[O + 38]), "+f"(d[O + 39]), "+f"(d[O + 40]), "+f"(d[O + 41]), "+f"(d[O + 42]), "+f"(d[O + 43]), "+f"(d[O + 44]), "+f"(d[O + 45]), "+f"(d[O + 46]), "+f"(d[O + 47]), "+f"(d[O + 48]), "+f"(d[O + 49]), "+f"(d[O + 50]), "+f"(d[O + 51]), "+f"(d[O + 52]), "+f"(d[O + 53]), "+f"(d[O + 54]), "+f"(d[O + 55]), "+f"(d[O + 56]), "+f"(d[O + 57]), "+f"(d[O + 58]), "+f"(d[O + 59]), "+f"(d[O + 60]), "+f"(d[O + 61]), "+f"(d[O + 62]), "+f"(d[O + 63]), "+f"(d[O + 64]), "+f"(d[O + 65]), "+f"(d[O + 66]), "+f"(d[O + 67]), "+f"(d[O + 68]), "+f"(d[O + 69]), "+f"(d[O + 70]), "+f"(d[O + 71])
    : "l"(da), "l"(db), "r"(sc), "n"(TA), "n"(TB));
}
template <int TA, int TB, int O, int T> __device__ __forceinline__ void wgmma_ss_n160(float (&d)[T], uint64_t da, uint64_t db, int sc) {
  asm volatile("{\n.reg .pred p;\nsetp.ne.b32 p, %82, 0;\n"
    "wgmma.mma_async.sync.aligned.m64n160k16.f32.bf16.bf16 {%0, %1, %2, %3, %4, %5, %6, %7, %8, %9, %10, %11, %12, %13, %14, %15, %16, %17, %18, %19, %20, %21, %22, %23, %24, %25, %26, %27, %28, %29, %30, %31, %32, %33, %34, %35, %36, %37, %38, %39, %40, %41, %42, %43, %44, %45, %46, %47, %48, %49, %50, %51, %52, %53, %54, %55, %56, %57, %58, %59, %60, %61, %62, %63, %64, %65, %66, %67, %68, %69, %70, %71, %72, %73, %74, %75, %76, %77, %78, %79}, %80, %81, p, 1, 1, %83, %84;\n}\n"
    : "+f"(d[O + 0]), "+f"(d[O + 1]), "+f"(d[O + 2]), "+f"(d[O + 3]), "+f"(d[O + 4]), "+f"(d[O + 5]), "+f"(d[O + 6]), "+f"(d[O + 7]), "+f"(d[O + 8]), "+f"(d[O + 9]), "+f"(d[O + 10]), "+f"(d[O + 11]), "+f"(d[O + 12]), "+f"(d[O + 13]), "+f"(d[O + 14]), "+f"(d[O + 15]), "+f"(d[O + 16]), "+f"(d[O + 17]), "+f"(d[O + 18]), "+f"(d[O + 19]), "+f"(d[O + 20]), "+f"(d[O + 21]), "+f"(d[O + 22]), "+f"(d[O + 23]), "+f"(d[O + 24]), "+f"(d[O + 25]), "+f"(d[O + 26]), "+f"(d[O + 27]), "+f"(d[O + 28]), "+f"(d[O + 29]), "+f"(d[O + 30]), "+f"(d[O + 31]), "+f"(d[O + 32]), "+f"(d[O + 33]), "+f"(d[O + 34]), "+f"(d[O + 35]), "+f"(d[O + 36]), "+f"(d[O + 37]), "+f"(d[O + 38]), "+f"(d[O + 39]), "+f"(d[O + 40]), "+f"(d[O + 41]), "+f"(d[O + 42]), "+f"(d[O + 43]), "+f"(d[O + 44]), "+f"(d[O + 45]), "+f"(d[O + 46]), "+f"(d[O + 47]), "+f"(d[O + 48]), "+f"(d[O + 49]), "+f"(d[O + 50]), "+f"(d[O + 51]), "+f"(d[O + 52]), "+f"(d[O + 53]), "+f"(d[O + 54]), "+f"(d[O + 55]), "+f"(d[O + 56]), "+f"(d[O + 57]), "+f"(d[O + 58]), "+f"(d[O + 59]), "+f"(d[O + 60]), "+f"(d[O + 61]), "+f"(d[O + 62]), "+f"(d[O + 63]), "+f"(d[O + 64]), "+f"(d[O + 65]), "+f"(d[O + 66]), "+f"(d[O + 67]), "+f"(d[O + 68]), "+f"(d[O + 69]), "+f"(d[O + 70]), "+f"(d[O + 71]), "+f"(d[O + 72]), "+f"(d[O + 73]), "+f"(d[O + 74]), "+f"(d[O + 75]), "+f"(d[O + 76]), "+f"(d[O + 77]), "+f"(d[O + 78]), "+f"(d[O + 79])
    : "l"(da), "l"(db), "r"(sc), "n"(TA), "n"(TB));
}
template <int TA, int TB, int O, int T> __device__ __forceinline__ void wgmma_ss_n192(float (&d)[T], uint64_t da, uint64_t db, int sc) {
  asm volatile("{\n.reg .pred p;\nsetp.ne.b32 p, %98, 0;\n"
    "wgmma.mma_async.sync.aligned.m64n192k16.f32.bf16.bf16 {%0, %1, %2, %3, %4, %5, %6, %7, %8, %9, %10, %11, %12, %13, %14, %15, %16, %17, %18, %19, %20, %21, %22, %23, %24, %25, %26, %27, %28, %29, %30, %31, %32, %33, %34, %35, %36, %37, %38, %39, %40, %41, %42, %43, %44, %45, %46, %47, %48, %49, %50, %51, %52, %53, %54, %55, %56, %57, %58, %59, %60, %61, %62, %63, %64, %65, %66, %67, %68, %69, %70, %71, %72, %73, %74, %75, %76, %77, %78, %79, %80, %81, %82, %83, %84, %85, %86, %87, %88, %89, %90, %91, %92, %93, %94, %95}, %96, %97, p, 1, 1, %99, %100;\n}\n"
    : "+f"(d[O + 0]), "+f"(d[O + 1]), "+f"(d[O + 2]), "+f"(d[O + 3]), "+f"(d[O + 4]), "+f"(d[O + 5]), "+f"(d[O + 6]), "+f"(d[O + 7]), "+f"(d[O + 8]), "+f"(d[O + 9]), "+f"(d[O + 10]), "+f"(d[O + 11]), "+f"(d[O + 12]), "+f"(d[O + 13]), "+f"(d[O + 14]), "+f"(d[O + 15]), "+f"(d[O + 16]), "+f"(d[O + 17]), "+f"(d[O + 18]), "+f"(d[O + 19]), "+f"(d[O + 20]), "+f"(d[O + 21]), "+f"(d[O + 22]), "+f"(d[O + 23]), "+f"(d[O + 24]), "+f"(d[O + 25]), "+f"(d[O + 26]), "+f"(d[O + 27]), "+f"(d[O + 28]), "+f"(d[O + 29]), "+f"(d[O + 30]), "+f"(d[O + 31]), "+f"(d[O + 32]), "+f"(d[O + 33]), "+f"(d[O + 34]), "+f"(d[O + 35]), "+f"(d[O + 36]), "+f"(d[O + 37]), "+f"(d[O + 38]), "+f"(d[O + 39]), "+f"(d[O + 40]), "+f"(d[O + 41]), "+f"(d[O + 42]), "+f"(d[O + 43]), "+f"(d[O + 44]), "+f"(d[O + 45]), "+f"(d[O + 46]), "+f"(d[O + 47]), "+f"(d[O + 48]), "+f"(d[O + 49]), "+f"(d[O + 50]), "+f"(d[O + 51]), "+f"(d[O + 52]), "+f"(d[O + 53]), "+f"(d[O + 54]), "+f"(d[O + 55]), "+f"(d[O + 56]), "+f"(d[O + 57]), "+f"(d[O + 58]), "+f"(d[O + 59]), "+f"(d[O + 60]), "+f"(d[O + 61]), "+f"(d[O + 62]), "+f"(d[O + 63]), "+f"(d[O + 64]), "+f"(d[O + 65]), "+f"(d[O + 66]), "+f"(d[O + 67]), "+f"(d[O + 68]), "+f"(d[O + 69]), "+f"(d[O + 70]), "+f"(d[O + 71]), "+f"(d[O + 72]), "+f"(d[O + 73]), "+f"(d[O + 74]), "+f"(d[O + 75]), "+f"(d[O + 76]), "+f"(d[O + 77]), "+f"(d[O + 78]), "+f"(d[O + 79]), "+f"(d[O + 80]), "+f"(d[O + 81]), "+f"(d[O + 82]), "+f"(d[O + 83]), "+f"(d[O + 84]), "+f"(d[O + 85]), "+f"(d[O + 86]), "+f"(d[O + 87]), "+f"(d[O + 88]), "+f"(d[O + 89]), "+f"(d[O + 90]), "+f"(d[O + 91]), "+f"(d[O + 92]), "+f"(d[O + 93]), "+f"(d[O + 94]), "+f"(d[O + 95])
    : "l"(da), "l"(db), "r"(sc), "n"(TA), "n"(TB));
}
template <int TB, int O, int T> __device__ __forceinline__ void wgmma_rs_n72(float (&d)[T], uint32_t a0, uint32_t a1, uint32_t a2, uint32_t a3, uint64_t db, int sc) {
  asm volatile("{\n.reg .pred p;\nsetp.ne.b32 p, %41, 0;\n"
    "wgmma.mma_async.sync.aligned.m64n72k16.f32.bf16.bf16 {%0, %1, %2, %3, %4, %5, %6, %7, %8, %9, %10, %11, %12, %13, %14, %15, %16, %17, %18, %19, %20, %21, %22, %23, %24, %25, %26, %27, %28, %29, %30, %31, %32, %33, %34, %35}, {%36, %37, %38, %39}, %40, p, 1, 1, %42;\n}\n"
    : "+f"(d[O + 0]), "+f"(d[O + 1]), "+f"(d[O + 2]), "+f"(d[O + 3]), "+f"(d[O + 4]), "+f"(d[O + 5]), "+f"(d[O + 6]), "+f"(d[O + 7]), "+f"(d[O + 8]), "+f"(d[O + 9]), "+f"(d[O + 10]), "+f"(d[O + 11]), "+f"(d[O + 12]), "+f"(d[O + 13]), "+f"(d[O + 14]), "+f"(d[O + 15]), "+f"(d[O + 16]), "+f"(d[O + 17]), "+f"(d[O + 18]), "+f"(d[O + 19]), "+f"(d[O + 20]), "+f"(d[O + 21]), "+f"(d[O + 22]), "+f"(d[O + 23]), "+f"(d[O + 24]), "+f"(d[O + 25]), "+f"(d[O + 26]), "+f"(d[O + 27]), "+f"(d[O + 28]), "+f"(d[O + 29]), "+f"(d[O + 30]), "+f"(d[O + 31]), "+f"(d[O + 32]), "+f"(d[O + 33]), "+f"(d[O + 34]), "+f"(d[O + 35])
    : "r"(a0), "r"(a1), "r"(a2), "r"(a3), "l"(db), "r"(sc), "n"(TB));
}
template <int TB, int O, int T> __device__ __forceinline__ void wgmma_rs_n80(float (&d)[T], uint32_t a0, uint32_t a1, uint32_t a2, uint32_t a3, uint64_t db, int sc) {
  asm volatile("{\n.reg .pred p;\nsetp.ne.b32 p, %45, 0;\n"
    "wgmma.mma_async.sync.aligned.m64n80k16.f32.bf16.bf16 {%0, %1, %2, %3, %4, %5, %6, %7, %8, %9, %10, %11, %12, %13, %14, %15, %16, %17, %18, %19, %20, %21, %22, %23, %24, %25, %26, %27, %28, %29, %30, %31, %32, %33, %34, %35, %36, %37, %38, %39}, {%40, %41, %42, %43}, %44, p, 1, 1, %46;\n}\n"
    : "+f"(d[O + 0]), "+f"(d[O + 1]), "+f"(d[O + 2]), "+f"(d[O + 3]), "+f"(d[O + 4]), "+f"(d[O + 5]), "+f"(d[O + 6]), "+f"(d[O + 7]), "+f"(d[O + 8]), "+f"(d[O + 9]), "+f"(d[O + 10]), "+f"(d[O + 11]), "+f"(d[O + 12]), "+f"(d[O + 13]), "+f"(d[O + 14]), "+f"(d[O + 15]), "+f"(d[O + 16]), "+f"(d[O + 17]), "+f"(d[O + 18]), "+f"(d[O + 19]), "+f"(d[O + 20]), "+f"(d[O + 21]), "+f"(d[O + 22]), "+f"(d[O + 23]), "+f"(d[O + 24]), "+f"(d[O + 25]), "+f"(d[O + 26]), "+f"(d[O + 27]), "+f"(d[O + 28]), "+f"(d[O + 29]), "+f"(d[O + 30]), "+f"(d[O + 31]), "+f"(d[O + 32]), "+f"(d[O + 33]), "+f"(d[O + 34]), "+f"(d[O + 35]), "+f"(d[O + 36]), "+f"(d[O + 37]), "+f"(d[O + 38]), "+f"(d[O + 39])
    : "r"(a0), "r"(a1), "r"(a2), "r"(a3), "l"(db), "r"(sc), "n"(TB));
}
template <int N, int TA, int TB, int O = 0, int T> __device__ __forceinline__ void wgmma_ss(float (&d)[T], uint64_t da, uint64_t db, int sc) {
  if constexpr (N == 24) wgmma_ss_n24<TA, TB, O, T>(d, da, db, sc);
  if constexpr (N == 72) wgmma_ss_n72<TA, TB, O, T>(d, da, db, sc);
  if constexpr (N == 80) wgmma_ss_n80<TA, TB, O, T>(d, da, db, sc);
  if constexpr (N == 96) wgmma_ss_n96<TA, TB, O, T>(d, da, db, sc);
  if constexpr (N == 144) wgmma_ss_n144<TA, TB, O, T>(d, da, db, sc);
  if constexpr (N == 160) wgmma_ss_n160<TA, TB, O, T>(d, da, db, sc);
  if constexpr (N == 192) wgmma_ss_n192<TA, TB, O, T>(d, da, db, sc);
}
template <int N, int TB, int O = 0, int T> __device__ __forceinline__ void wgmma_rs(float (&d)[T], uint32_t a0, uint32_t a1, uint32_t a2, uint32_t a3, uint64_t db, int sc) {
  if constexpr (N == 72) wgmma_rs_n72<TB, O, T>(d, a0, a1, a2, a3, db, sc);
  if constexpr (N == 80) wgmma_rs_n80<TB, O, T>(d, a0, a1, a2, a3, db, sc);
}


namespace {

constexpr int NTHREADS = 384;
constexpr int NCTA = 132;

constexpr int SKEW1 = 2, SKEW4 = 4, SKEW5 = 4;

constexpr int STAGE = 36864, NST = 5;
constexpr int OFF_H = NST * STAGE;
constexpr int OFF_E = OFF_H + 18432;
constexpr int P1_STAGE = 16384 + 24576 + 3072;
constexpr int OFF_CSP = 176128;
constexpr int OFF_T = 210176;
constexpr int OFF_BARS = 227840;
constexpr int OFF_CS = OFF_BARS + 512;
constexpr int OFF_LN = OFF_CS + 896;
constexpr int SMEM_BYTES = OFF_LN + 1024 + 1024;
constexpr int OFF_PK = 147456, PK_CS = 1056, PV_V = 20 * PK_CS, PV_BYTES = PV_V + 10240;
constexpr int OFF_X = 207872;
constexpr int OFF_KVS = OFF_PK;
constexpr int OFF_KVB = OFF_PK + 14720;
constexpr int OFF_O = 165888;

enum { B_P1F = 0, B_P1E = 4, B_OF = 8, B_RF = 17, B_WO = 22, B_CS = 23, B_ACK = 24, B_P3DONE = 27,
       B_RE = 28, B_P1DONE = 33, B_P2DONE = 34, B_EFREE = 35, B_P3K = 36, NBARS = 40,
       B_RED = 40, B_GO = 44, B_KVL = 45, B_X = 46, B_TFREE = 47 };

__device__ __align__(1024) uint8_t g_wo[4 * 72 * 2304];
__device__ __align__(1024) uint8_t g_o[32 * 72 * 1024];
__device__ __align__(1024) uint8_t g_hn[32 * 576 * 128];
__device__ __align__(1024) uint8_t g_u[72 * 576 * 128];
constexpr int KV_BYTES = 4 * 3680;
__device__ __align__(1024) uint8_t g_kv[8 * KV_BYTES];
__device__ __align__(1024) uint4 g_mb[128 * 72];
__device__ __align__(1024) unsigned g_cnt[64 * 32];
enum { C_CS = 0, C_KV = 8, C_O = 16, C_WO = 48, C_H = 49, C_U = 51, C_UF = 53, C_HF = 55, C_UE = 56 };

__device__ __forceinline__ uint32_t smem_u32(const void* p) { return (uint32_t)__cvta_generic_to_shared(p); }
__device__ __forceinline__ void mbar_init(uint32_t bar, int cnt) { asm volatile("mbarrier.init.shared::cta.b64 [%0], %1;" ::"r"(bar), "r"(cnt) : "memory"); }
__device__ __forceinline__ void mbar_expect_tx(uint32_t bar, int bytes) { asm volatile("mbarrier.arrive.expect_tx.shared::cta.b64 _, [%0], %1;" ::"r"(bar), "r"(bytes) : "memory"); }
__device__ __forceinline__ void mbar_arrive(uint32_t bar) { asm volatile("mbarrier.arrive.shared::cta.b64 _, [%0];" ::"r"(bar) : "memory"); }
__device__ __forceinline__ void mbar_arrive_remote(uint32_t a) { asm volatile("mbarrier.arrive.shared::cluster.b64 _, [%0];" ::"r"(a) : "memory"); }
__device__ __forceinline__ void mbar_wait(uint32_t bar, int parity) {
  asm volatile(
      "{\n.reg .pred p;\n.reg .u32 c;\nmov.u32 c, 0;\n"
      "LAB_WAIT:\n"
      "mbarrier.try_wait.parity.shared::cta.b64 p, [%0], %1;\n"
      "@p bra DONE;\n"
      "add.u32 c, c, 1;\nsetp.lt.u32 p, c, 2000000;\n@p bra LAB_WAIT;\ntrap;\n"
      "DONE:\n}" ::"r"(bar), "r"(parity) : "memory");
}
__device__ __forceinline__ bool elect_one() {
  uint32_t pred;
  asm volatile("{\n.reg .pred p;\nelect.sync _|p, 0xffffffff;\nselp.u32 %0, 1, 0, p;\n}" : "=r"(pred));
  return pred != 0;
}
__device__ __forceinline__ void bulk_load(uint32_t dst, const void* src, int bytes, uint32_t bar) {
  asm volatile("cp.async.bulk.shared::cluster.global.mbarrier::complete_tx::bytes [%0], [%1], %2, [%3];" ::"r"(dst), "l"(src), "r"(bytes), "r"(bar) : "memory");
}
__device__ __forceinline__ void bulk_store(void* dst, uint32_t src, int bytes) {
  asm volatile("cp.async.bulk.global.shared::cta.bulk_group [%0], [%1], %2;" ::"l"(dst), "r"(src), "r"(bytes) : "memory");
}
__device__ __forceinline__ void bulk_reduce_f32(void* dst, uint32_t src, int bytes) {
  asm volatile("cp.reduce.async.bulk.global.shared::cta.bulk_group.add.f32 [%0], [%1], %2;" ::"l"(dst), "r"(src), "r"(bytes) : "memory");
}
__device__ __forceinline__ void l2_prefetch(const void* src, int bytes) {
  asm volatile("cp.async.bulk.prefetch.L2.global [%0], %1;" ::"l"(src), "r"(bytes) : "memory");
}
__device__ __forceinline__ void bulk_commit_wait() { asm volatile("cp.async.bulk.commit_group;\ncp.async.bulk.wait_group 0;" ::: "memory"); }
__device__ __forceinline__ void bulk_commit_wait_read() { asm volatile("cp.async.bulk.commit_group;\ncp.async.bulk.wait_group.read 0;" ::: "memory"); }
__device__ __forceinline__ void tma2d(uint32_t dst, const CUtensorMap* m, uint32_t bar, int c0, int c1) {
  asm volatile("cp.async.bulk.tensor.2d.shared::cluster.global.mbarrier::complete_tx::bytes [%0], [%1, {%3, %4}], [%2];" ::"r"(dst), "l"(m), "r"(bar), "r"(c0), "r"(c1) : "memory");
}
__device__ __forceinline__ void tma3d(uint32_t dst, const CUtensorMap* m, uint32_t bar, int c0, int c1, int c2) {
  asm volatile("cp.async.bulk.tensor.3d.shared::cluster.global.mbarrier::complete_tx::bytes [%0], [%1, {%3, %4, %5}], [%2];" ::"r"(dst), "l"(m), "r"(bar), "r"(c0), "r"(c1), "r"(c2) : "memory");
}
__device__ __forceinline__ void tma3d_mc(uint32_t dst, const CUtensorMap* m, uint32_t bar, int c0, int c1, int c2) {
  asm volatile("cp.async.bulk.tensor.3d.shared::cluster.global.mbarrier::complete_tx::bytes.multicast::cluster [%0], [%1, {%3, %4, %5}], [%2], %6;"
               ::"r"(dst), "l"(m), "r"(bar), "r"(c0), "r"(c1), "r"(c2), "h"((uint16_t)3) : "memory");
}
__device__ __forceinline__ void fence_async_gl() { asm volatile("fence.proxy.async.global;" ::: "memory"); }
__device__ __forceinline__ void fence_async_smem() { asm volatile("fence.proxy.async.shared::cta;" ::: "memory"); }
__device__ __forceinline__ void bar_sync(int id, int n) { asm volatile("bar.sync %0, %1;" ::"r"(id), "r"(n) : "memory"); }
__device__ __forceinline__ void bar_arrive(int id, int n) { asm volatile("bar.arrive %0, %1;" ::"r"(id), "r"(n) : "memory"); }
__device__ __forceinline__ void signal_release(int c) { asm volatile("red.release.gpu.global.add.u32 [%0], 1;" ::"l"(&g_cnt[c * 32]) : "memory"); }
__device__ __forceinline__ void signal_relaxed(int c) { asm volatile("red.relaxed.gpu.global.add.u32 [%0], 1;" ::"l"(&g_cnt[c * 32]) : "memory"); }
__device__ __forceinline__ void publish_fence() { asm volatile("fence.release.gpu;" ::: "memory"); }
__device__ __forceinline__ void wait_cnt(int c, unsigned target) {
  unsigned v; int it = 0;
  do {
    asm volatile("ld.relaxed.gpu.global.u32 %0, [%1];" : "=r"(v) : "l"(&g_cnt[c * 32]) : "memory");
    if (++it > 4000000) break;
  } while ((int)(v - target) < 0);
}
__device__ __forceinline__ unsigned load_cnt(int c, int i = 0) {
  unsigned v; asm volatile("ld.relaxed.gpu.global.u32 %0, [%1];" : "=r"(v) : "l"(&g_cnt[c * 32 + i]) : "memory"); return v;
}
__device__ __forceinline__ void cluster_arrive() { asm volatile("barrier.cluster.arrive.relaxed.aligned;" ::: "memory"); }
__device__ __forceinline__ void cluster_wait() { asm volatile("barrier.cluster.wait.aligned;" ::: "memory"); }
__device__ __forceinline__ void wg_fence() { asm volatile("wgmma.fence.sync.aligned;" ::: "memory"); }
__device__ __forceinline__ void wg_commit() { asm volatile("wgmma.commit_group.sync.aligned;" ::: "memory"); }
template <int N> __device__ __forceinline__ void wg_wait() { asm volatile("wgmma.wait_group.sync.aligned %0;" ::"n"(N) : "memory"); }
template <int N> __device__ __forceinline__ void zero_acc(float (&d)[N]) {
#pragma unroll
  for (int i = 0; i < N; i++) d[i] = 0.f;
}
template <int N> __device__ __forceinline__ void reg_fence(float (&d)[N]) {
#pragma unroll
  for (int i = 0; i < N; i++) asm volatile("" : "+f"(d[i])::"memory");
}
__device__ __forceinline__ uint32_t pack_bf16(float lo, float hi) {
  uint32_t r; asm("cvt.rn.bf16x2.f32 %0, %1, %2;" : "=r"(r) : "f"(hi), "f"(lo)); return r;
}
__device__ __forceinline__ float bf_lo(uint32_t v) { return __uint_as_float(v << 16); }
__device__ __forceinline__ float bf_hi(uint32_t v) { return __uint_as_float(v & 0xffff0000u); }
__device__ __forceinline__ float ex2(float x) { float y; asm("ex2.approx.ftz.f32 %0, %1;" : "=f"(y) : "f"(x)); return y; }
__device__ __forceinline__ float rcp(float x) { float y; asm("rcp.approx.ftz.f32 %0, %1;" : "=f"(y) : "f"(x)); return y; }
__device__ __forceinline__ float tanh_fast(float x) { float y; asm("tanh.approx.f32 %0, %1;" : "=f"(y) : "f"(x)); return y; }
__device__ __forceinline__ void sts128(uint32_t a, uint32_t x, uint32_t y, uint32_t z, uint32_t w) {
  asm volatile("st.shared.v4.b32 [%0], {%1, %2, %3, %4};" ::"r"(a), "r"(x), "r"(y), "r"(z), "r"(w) : "memory");
}
__device__ __forceinline__ void sts64(uint32_t a, uint32_t x, uint32_t y) { asm volatile("st.shared.v2.b32 [%0], {%1, %2};" ::"r"(a), "r"(x), "r"(y) : "memory"); }
__device__ __forceinline__ void sts32f(uint32_t a, float x) { asm volatile("st.shared.f32 [%0], %1;" ::"r"(a), "f"(x) : "memory"); }
__device__ __forceinline__ void sts16(uint32_t a, uint32_t x) { asm volatile("st.shared.b16 [%0], %1;" ::"r"(a), "h"((uint16_t)x) : "memory"); }
__device__ __forceinline__ void stsm_x4(uint32_t a, uint32_t r0, uint32_t r1, uint32_t r2, uint32_t r3) {
  asm volatile("stmatrix.sync.aligned.m8n8.x4.shared.b16 [%0], {%1, %2, %3, %4};" ::"r"(a), "r"(r0), "r"(r1), "r"(r2), "r"(r3) : "memory");
}
__device__ __forceinline__ void stsm_x1(uint32_t a, uint32_t r0) {
  asm volatile("stmatrix.sync.aligned.m8n8.x1.shared.b16 [%0], {%1};" ::"r"(a), "r"(r0) : "memory");
}
__device__ __forceinline__ void ldsm_x4(uint32_t a, uint32_t& r0, uint32_t& r1, uint32_t& r2, uint32_t& r3) {
  asm volatile("ldmatrix.sync.aligned.m8n8.x4.shared.b16 {%0, %1, %2, %3}, [%4];" : "=r"(r0), "=r"(r1), "=r"(r2), "=r"(r3) : "r"(a) : "memory");
}
__device__ __forceinline__ void ldsm_x4_t(uint32_t a, uint32_t& r0, uint32_t& r1, uint32_t& r2, uint32_t& r3) {
  asm volatile("ldmatrix.sync.aligned.m8n8.x4.trans.shared.b16 {%0, %1, %2, %3}, [%4];" : "=r"(r0), "=r"(r1), "=r"(r2), "=r"(r3) : "r"(a) : "memory");
}
__device__ __forceinline__ uint32_t mapa(uint32_t a, uint32_t cta) {
  uint32_t r; asm("mapa.shared::cluster.u32 %0, %1, %2;" : "=r"(r) : "r"(a), "r"(cta)); return r;
}
__device__ __forceinline__ uint4 ld_relaxed_v4(const void* p) {
  uint4 v; asm volatile("ld.relaxed.gpu.global.v4.u32 {%0, %1, %2, %3}, [%4];" : "=r"(v.x), "=r"(v.y), "=r"(v.z), "=r"(v.w) : "l"(p) : "memory"); return v;
}
__device__ __forceinline__ void st_relaxed_v4(void* p, uint32_t x, uint32_t y, uint32_t z, uint32_t w) {
  asm volatile("st.relaxed.gpu.global.v4.u32 [%0], {%1, %2, %3, %4};" ::"l"(p), "r"(x), "r"(y), "r"(z), "r"(w) : "memory");
}
__device__ __forceinline__ uint32_t ldg_nc(const uint32_t* p) {
  uint32_t v; asm volatile("ld.global.nc.u32 %0, [%1];" : "=r"(v) : "l"(p)); return v;
}
__device__ __forceinline__ uint32_t ldg_nc_u16(const void* p) {
  uint16_t v; asm volatile("ld.global.nc.u16 %0, [%1];" : "=h"(v) : "l"(p)); return v;
}
__device__ __forceinline__ uint4 ldg_nc_v4(const uint4* p) {
  uint4 v; asm volatile("ld.global.nc.v4.u32 {%0, %1, %2, %3}, [%4];" : "=r"(v.x), "=r"(v.y), "=r"(v.z), "=r"(v.w) : "l"(p)); return v;
}
__device__ __forceinline__ float quad_sum(float v) { v += __shfl_xor_sync(~0u, v, 1); v += __shfl_xor_sync(~0u, v, 2); return v; }

__device__ __forceinline__ constexpr uint64_t desc_hi(int lbo, int sbo, int sw) {
  return ((uint64_t)sw << 62) | ((uint64_t)(sbo >> 4) << 32) | ((uint64_t)(lbo >> 4) << 16);
}
__device__ __forceinline__ uint64_t mkdesc(uint64_t hi, uint32_t addr) { return hi | (uint64_t)((addr & 0x3FFFF) >> 4); }
constexpr uint64_t D_SW128 = desc_hi(8192, 1024, 1);
constexpr uint64_t D_NCORE = desc_hi(128, 1024, 0);

__device__ __forceinline__ uint32_t slot(int s) { return s == NST - 1 ? 0u : (uint32_t)(s + 1) * STAGE; }

struct Params {
  const __nv_bfloat16 *wqkv, *wphi, *b1, *b2;
};

template <int HR> __device__ __forceinline__ void featmap(const float (&p)[36], float rs, uint32_t (&o)[18]) {
  const float L2E = 1.4426950408889634f * rs;
  float mx = fmaxf(p[HR], p[HR + 1]), mn = fminf(p[HR], p[HR + 1]);
#pragma unroll
  for (int j = 1; j < 9; j++) {
    mx = fmaxf(mx, fmaxf(p[4 * j + HR], p[4 * j + HR + 1]));
    mn = fminf(mn, fminf(p[4 * j + HR], p[4 * j + HR + 1]));
  }
  float a[18], b[18], sa = 0.f, sb = 0.f;
  const float mxs = -mx * L2E, mns = mn * L2E;
#pragma unroll
  for (int i = 0; i < 18; i++) {
    float v = p[4 * (i >> 1) + HR + (i & 1)];
    a[i] = ex2(fmaf(v, L2E, mxs)); sa += a[i];
    b[i] = ex2(fmaf(v, -L2E, mns)); sb += b[i];
  }
  const float ra = rcp(sa), rb = rcp(sb);
#pragma unroll
  for (int i = 0; i < 9; i++) {
    o[i] = pack_bf16(a[2 * i] * ra, a[2 * i + 1] * ra);
    o[9 + i] = pack_bf16(b[2 * i] * rb, b[2 * i + 1] * rb);
  }
}

__device__ __forceinline__ float gelu(float h) {
  float t = tanh_fast(h * fmaf(h * h, 8.f * 0.0356774081363f, 2.f * 0.7978845608028654f));
  return fmaf(h, t, h);
}

__device__ __forceinline__ constexpr int qkv_idx(int part, int j) { return j < 8 ? part * 32 + 4 * j : 96 + 4 * part; }

__global__ void __cluster_dims__(2, 1, 1) __launch_bounds__(NTHREADS, 1)
fused_kernel(const __grid_constant__ CUtensorMap mX, const __grid_constant__ CUtensorMap mWm, const __grid_constant__ CUtensorMap mWr,
             const __grid_constant__ CUtensorMap mXr, const __grid_constant__ CUtensorMap mWo,
             const __grid_constant__ CUtensorMap mW1a, const __grid_constant__ CUtensorMap mW1b,
             const __grid_constant__ CUtensorMap mW2, const __grid_constant__ CUtensorMap mOut, const Params p) {
  extern __shared__ uint8_t smem_raw[];
  const uint32_t sraw = smem_u32(smem_raw);
  const uint32_t sb = (sraw + 1023) & ~1023u;
  uint8_t* smem = smem_raw + (sb - sraw);
  const uint32_t bars = sb + OFF_BARS;
  const int warp = __shfl_sync(~0u, threadIdx.x >> 5, 0), lane = threadIdx.x & 31;
  const int rank = blockIdx.x & 1;
  int pp;
  {
    int c = blockIdx.x >> 1;
    if (c < 4) pp = 60 + c;
    else if (c < 36) pp = 4 * ((c - 4) & 7) + ((c - 4) >> 3);
    else if (c < 64) pp = 32 + 4 * ((c - 36) % 7) + (c - 36) / 7;
    else pp = c;
  }
  const int L = 2 * pp + rank;
  const bool act = L < 128;
  const int p1_r = ((L >> 3) & 7) * 2 + (L & 1), p1_g = ((L >> 6) & 1) * 4 + ((L >> 1) & 3);
  if (warp == 9) {
    if (elect_one()) {
      if (act) l2_prefetch(p.wqkv + (size_t)L * 2 * 1728, 2 * 3456);
#pragma unroll
      for (int i = 8; i < 24; i++) mbar_init(bars + 8 * i, i == B_CS ? 96 : 1);
      asm volatile("fence.mbarrier_init.release.cluster;" ::: "memory");
      fence_async_smem();
    }
    __syncwarp();
  } else if (warp == 10) {
    if (elect_one()) {
#pragma unroll
      for (int i = 24; i < NBARS; i++) mbar_init(bars + 8 * i, i == B_ACK ? 4 : (i == B_P1DONE ? 8 : (i >= B_RE ? 2 : 1)));
      asm volatile("fence.mbarrier_init.release.cluster;" ::: "memory");
      fence_async_smem();
    }
    __syncwarp();
  } else if (warp == 11) {
    if (elect_one()) {
#pragma unroll
      for (int i = 0; i < 8; i++) mbar_init(bars + 8 * (B_RED + i), B_RED + i == B_TFREE ? 8 : 1);
      asm volatile("fence.mbarrier_init.release.cluster;" ::: "memory");
      fence_async_smem();
    }
    __syncwarp();
    if (lane < 4) mbar_expect_tx(bars + 8 * (B_RED + lane), 4608);
    __syncwarp();
  }
  if (warp != 8) cluster_arrive();
  const int p4_fg = L / 11, p4_j = L % 11;
  const bool p4_main = p4_j < 9;
  const int p4_fb = p4_main ? (p4_fg * 6 + (p4_j / 3) * 2) : (p4_fg * 6 + (p4_j - 9) * 3);
  const int p4_d0 = p4_main ? (p4_j % 3) * 160 : 480;
  const int p5_sb = pp >> 2, p5_db = pp & 3;
  const int p3_b = p5_sb * 2 + rank, p3_db = p5_db;

  if (warp >= 8) {
    asm volatile("setmaxnreg.dec.sync.aligned.u32 104;");
    if (warp == 8) {
      const bool el = elect_one();
      if (el) {
        asm volatile("prefetch.tensormap [%0];" ::"l"(&mX) : "memory");
        asm volatile("prefetch.tensormap [%0];" ::"l"(&mWm) : "memory");
        asm volatile("prefetch.tensormap [%0];" ::"l"(&mWr) : "memory");
#pragma unroll
        for (int i = 0; i < 8; i++) mbar_init(bars + 8 * i, i < B_P1E ? 1 : 4);
        asm volatile("fence.mbarrier_init.release.cluster;" ::: "memory");
        fence_async_smem();
      }
      __syncwarp();
      cluster_arrive();
      if (el && act) {
        mbar_expect_tx(bars + 8 * B_P1F, P1_STAGE);
        tma2d(sb, &mX, bars + 8 * B_P1F, 0, p1_r * 128);
      }
      __syncwarp();
      cluster_wait();
      bar_arrive(8, 288);
      bar_arrive(9, 128);
      if (el) {
        unsigned ep1 = 0;
        if (!act) {
#pragma unroll 1
          for (int i = 0; i < 16; i++) {
            if (!(i & 1)) mbar_expect_tx(bars + 8 * (B_OF + (i >> 1)), 2 * 10368);
            tma2d(sb + i * 10368, &mWo, bars + 8 * (B_OF + (i >> 1)), (L - 128) * 144 + (i & 1) * 72, (i >> 1) * 72);
          }
          ep1 = load_cnt(C_U + 1) / 132 + 1;
          mbar_wait(bars + 8 * B_P1DONE, 0);
        }
        if (act) {
#pragma unroll 1
          for (int kb = 0; kb < 9; kb++) {
            int s = kb & 3;
            uint32_t fb = bars + 8 * (B_P1F + s), st = sb + s * P1_STAGE;
            const int k0 = kb * 64;
            if (kb >= 4) mbar_wait(bars + 8 * (B_P1E + s), ((kb >> 2) - 1) & 1);
            if (kb > 0) {
              mbar_expect_tx(fb, P1_STAGE);
              tma2d(st, &mX, fb, k0, p1_r * 128);
            }
            tma3d_mc(st + 16384 + rank * 12288, &mWm, fb, p1_g * 72, k0 + rank * 32, 0);
            tma3d_mc(st + 40960 + rank * 1536, &mWr, fb, p1_g * 72 + 64, k0 + rank * 32, 0);
            if (kb == 3) { l2_prefetch(p.wqkv + (size_t)256 * 1728 + L * 4320, 8640); ep1 = load_cnt(C_O + p3_b, p1_g) + 1; }
          }
          asm volatile("prefetch.tensormap [%0];" ::"l"(&mXr) : "memory");
          asm volatile("prefetch.tensormap [%0];" ::"l"(p4_main ? &mW1a : &mW1b) : "memory");
          wait_cnt(C_WO, ep1 * 32);
          fence_async_gl();
          mbar_wait(bars + 8 * B_P1DONE, 0);
          mbar_expect_tx(bars + 8 * B_WO, 8 * 18432);
#pragma unroll 1
          for (int kb = 0; kb < 8; kb++) bulk_load(sb + kb * 18432, g_wo + (size_t)(p3_db * 9 + kb) * 18432, 18432, bars + 8 * B_WO);
          mbar_wait(bars + 8 * B_TFREE, 0);
          mbar_expect_tx(bars + 8 * B_X, 18432);
          tma2d(sb + OFF_X, &mXr, bars + 8 * B_X, p3_db * 144, p3_b * 64);
          mbar_wait(bars + 8 * B_P2DONE, 0);
          mbar_expect_tx(bars + 8 * (B_OF + 8), 8192 + 18432);
          bulk_load(sb + 8 * 18432, g_wo + (size_t)(p3_db * 9 + 8) * 18432, 18432, bars + 8 * (B_OF + 8));
          {
            int kb = 0, it = 0;
            while (kb < 9) {
              const uint4 f0 = ld_relaxed_v4(&g_cnt[(C_O + p3_b) * 32]), f1 = ld_relaxed_v4(&g_cnt[(C_O + p3_b) * 32 + 4]);
              const unsigned m = (f0.x == ep1) | (f0.y == ep1) << 1 | (f0.z == ep1) << 2 | (f0.w == ep1) << 3 |
                                 (f1.x == ep1) << 4 | (f1.y == ep1) << 5 | (f1.z == ep1) << 6 | (f1.w == ep1) * 0x180;
              const int ready = ++it > 2000000 ? 9 : __ffs(~m) - 1;
              fence_async_gl();
#pragma unroll 1
              for (; kb < ready; kb++) {
                if (kb == 7) mbar_wait(bars + 8 * B_P3K, 0);
                if (kb < 8) mbar_expect_tx(bars + 8 * (B_OF + kb), 8192);
                bulk_load(sb + (kb < 7 ? OFF_O + kb * 8192 : (kb - 7) * 8192), g_o + (size_t)(p3_b * 9 + kb) * 8192, 8192, bars + 8 * (B_OF + kb));
              }
            }
          }
        }
        const int abytes4 = p4_main ? 16384 : 24576, bbytes4 = STAGE - abytes4;
        const CUtensorMap* m4 = p4_main ? &mW1a : &mW1b;
        int s = 0, ph = 1;
#pragma unroll 1
        for (int kb = 0; kb < 32; kb++) {
          uint32_t fb = bars + 8 * (B_RF + s);
          if (kb < 3) { if (act) mbar_wait(bars + 8 * (B_P3K + 1 + kb), 0); }
          else mbar_wait(bars + 8 * (B_RE + s), ph);
          mbar_expect_tx(fb, STAGE);
          const int kk = kb < 3 ? 2 * kb : (kb < 6 ? 2 * kb - 5 : kb);
          tma3d(sb + slot(s), m4, fb, 0, kk * 64, p4_fb);
          if (kb == 3) { wait_cnt(C_H, ep1 * 128); fence_async_gl(); }
          if (kb == 24) { asm volatile("prefetch.tensormap [%0];" ::"l"(&mOut) : "memory"); asm volatile("prefetch.tensormap [%0];" ::"l"(&mW2) : "memory"); }
          if (kb >= 3) bulk_load(sb + slot(s) + abytes4, g_hn + ((size_t)kk * 576 + p4_d0) * 128, bbytes4, fb);
          if (kb == 2) {
            if (act) mbar_wait(bars + 8 * B_P3DONE, 0);
            wait_cnt(C_HF, ep1 * 12);
            fence_async_gl();
#pragma unroll 1
            for (int q = 0; q < 3; q++) bulk_load(sb + slot(q) + abytes4, g_hn + ((size_t)q * 2 * 576 + p4_d0) * 128, bbytes4, bars + 8 * (B_RF + q));
          }
          if (++s == NST) { s = 0; ph ^= 1; }
        }
        if (act) {
          const int s0 = s;
#pragma unroll 1
          for (int kb = 0; kb < 36; kb++) {
            uint32_t fb = bars + 8 * (B_RF + s);
            const int kk = rank * 36 + (kb < 6 ? 2 * kb : (kb < 12 ? 2 * kb - 11 : kb));
            mbar_wait(bars + 8 * (B_RE + s), ph);
            mbar_expect_tx(fb, 16384 + 18432);
            tma3d(sb + slot(s), &mW2, fb, 0, kk * 64, p5_sb * 2);
            if (kb == 6) { wait_cnt(C_U + rank, ep1 * 132); fence_async_gl(); }
            if (kb >= NST) bulk_load(sb + slot(s) + 16384, g_u + ((size_t)kk * 576 + p5_db * 144) * 128, 18432, fb);
            if (kb == NST - 1) {
              wait_cnt(C_UE + rank, ep1 * 8);
              fence_async_gl();
              int q = s0;
#pragma unroll 1
              for (int i = 0; i < NST; i++) {
                if (i == 2) { wait_cnt(C_UF + rank, ep1 * 26); fence_async_gl(); }
                bulk_load(sb + slot(q) + 16384, g_u + ((size_t)(rank * 36 + 2 * i) * 576 + p5_db * 144) * 128, 18432, bars + 8 * (B_RF + q));
                if (++q == NST) q = 0;
              }
            }
            if (++s == NST) { s = 0; ph ^= 1; }
          }
        }
      }
    } else {
      const int tid = threadIdx.x - 288, aw = warp - 9;
      bar_sync(9, 128);
      unsigned ep1 = 0;
      if (act) {
        uint4 cv[12];
        mbar_wait(bars + 8 * B_GO, 0);
        if (lane < 27) {
          const uint4* src = reinterpret_cast<const uint4*>(p.wqkv + (size_t)(p1_r * 36 + aw * 12) * 1728 + (lane / 9) * 576 + p1_g * 72) + lane % 9;
#pragma unroll
          for (int i = 0; i < 12; i++) cv[i] = ldg_nc_v4(src + i * 216);
        }
        ep1 = (load_cnt(C_KV + p1_g) >> 4) + 1;
        if (lane < 27) {
          float cs[8];
#pragma unroll
          for (int i = 0; i < 8; i++) cs[i] = 0.f;
#pragma unroll
          for (int i = 0; i < 12; i++) {
            cs[0] += bf_lo(cv[i].x); cs[1] += bf_hi(cv[i].x); cs[2] += bf_lo(cv[i].y); cs[3] += bf_hi(cv[i].y);
            cs[4] += bf_lo(cv[i].z); cs[5] += bf_hi(cv[i].z); cs[6] += bf_lo(cv[i].w); cs[7] += bf_hi(cv[i].w);
          }
          float4* dst = reinterpret_cast<float4*>(smem + OFF_CSP + aw * 864 + lane * 32);
          dst[0] = make_float4(cs[0], cs[1], cs[2], cs[3]); dst[1] = make_float4(cs[4], cs[5], cs[6], cs[7]);
        }
        bar_sync(4, 96);
        if (tid < 72) {
          const float* c = reinterpret_cast<const float*>(smem + OFF_CSP) + tid * 3;
          float c0 = 0.f, c1 = 0.f, c2 = 0.f;
#pragma unroll
          for (int i = 0; i < 3; i++) { c0 += c[i * 216]; c1 += c[i * 216 + 1]; c2 += c[i * 216 + 2]; }
          st_relaxed_v4(g_mb + L * 72 + tid, __float_as_uint(c0), __float_as_uint(c1), __float_as_uint(c2), ep1);
          uint4 v[16];
          bool ok; int it = 0;
          mbar_wait(bars + 8 * (B_P1E + 3), 0);
          do {
#pragma unroll
            for (int i = 0; i < 16; i++) v[i] = ld_relaxed_v4(g_mb + ((L & 0x46) + (i >> 1) * 8 + (i & 1)) * 72 + tid);
            ok = true;
#pragma unroll
            for (int i = 0; i < 16; i++) ok = ok && v[i].w == ep1;
          } while (!ok && ++it < 1000000);
          c0 = c1 = c2 = 0.f;
#pragma unroll
          for (int i = 0; i < 16; i++) { c0 += __uint_as_float(v[i].x); c1 += __uint_as_float(v[i].y); c2 += __uint_as_float(v[i].z); }
          float* d = reinterpret_cast<float*>(smem + OFF_CS) + tid * 3;
          d[0] = c0; d[1] = c1; d[2] = c2;
          if (tid == 0) *reinterpret_cast<unsigned*>(smem + OFF_CS + 864) = ep1;
        }
        mbar_arrive(bars + 8 * B_CS);
      }
      __syncwarp();
      if (act && aw == 0) {
        if (lane == 0) wait_cnt(C_CS, ep1 * 4);
        bar_sync(3, 256 + 32);
        if (lane == 0) {
          bulk_reduce_f32(g_kv + p1_g * KV_BYTES, sb + OFF_KVS, KV_BYTES);
          bulk_commit_wait();
          signal_relaxed(C_KV + p1_g);
          mbar_expect_tx(bars + 8 * B_KVL, KV_BYTES);
          wait_cnt(C_KV + p1_g, ep1 * 16);
          fence_async_gl();
          bulk_load(sb + OFF_KVS, g_kv + p1_g * KV_BYTES, KV_BYTES, bars + 8 * B_KVL);
        }
      }
      if (aw >= 1) {
        const int wg = aw - 1;
        __syncwarp();
        bar_sync(14 + wg, 128 + 32);
        if (lane == 0) {
          publish_fence();
          if (p4_fg % 6 == 0 && (p4_j == 9 || (p4_j < 6 && wg == 0))) signal_relaxed(C_UE + (p4_fg >= 6));
          if (p4_fg % 6 < 2 && (wg == 0 || !p4_main)) signal_relaxed(C_UF + (p4_fg >= 6));
          signal_relaxed(C_U + (p4_fg >= 6));
          mbar_arrive_remote(mapa(bars + 8 * B_EFREE, rank ^ 1));
        }
      }
    }
  } else {
    asm volatile("setmaxnreg.inc.sync.aligned.u32 200;");
    const int wg = warp >> 2, wq = warp & 3, tw = threadIdx.x & 127;
    const int t4 = lane & 3, r8 = lane >> 2;
    bar_sync(8, 288);
    if (!act) {
      float4* z = reinterpret_cast<float4*>(g_kv) + (L - 128) * 1840 + threadIdx.x;
#pragma unroll
      for (int i = 0; i < 8; i++) if (i < 7 || threadIdx.x < 48) z[i * 256] = make_float4(0.f, 0.f, 0.f, 0.f);
      bar_sync(5, 256);
      if (threadIdx.x == 0) signal_release(C_CS);
      mbar_wait(bars + 8 * (B_OF + warp), 0);
      const uint32_t wi = sb + warp * 20736 + (18 * ((lane >> 1) & 3) + (lane & 1)) * 144 + (lane >> 3) * 16;
      const uint32_t wo = sb + 165888 + warp * 4608;
#pragma unroll 1
      for (int j = 0; j < 9; j++) {
        if (lane == 0) asm volatile("cp.async.bulk.wait_group.read 1;" ::: "memory");
        __syncwarp();
        const uint32_t ob = wo + (j & 1) * 2304;
#pragma unroll
        for (int hf = 0; hf < 2; hf++) {
          uint32_t r0, r1, r2, r3;
#pragma unroll
          for (int q = 0; q < 3; q++) {
            ldsm_x4_t(wi + hf * 10368 + j * 288 + (q < 2 ? q * 64 : 80), r0, r1, r2, r3);
            if (q < 2) stsm_x4(ob + hf * 1152 + q * 512 + lane * 16, r0, r1, r2, r3);
            else stsm_x1(ob + hf * 1152 + 1024 + lane * 16, r3);
          }
        }
        fence_async_smem();
        __syncwarp();
        if (lane == 0) {
          bulk_store(g_wo + (size_t)((L - 128) * 72 + warp * 9 + j) * 2304, ob, 2304);
          asm volatile("cp.async.bulk.commit_group;" ::: "memory");
        }
      }
      if (lane == 0) {
        asm volatile("cp.async.bulk.wait_group 0;" ::: "memory");
        publish_fence();
        signal_relaxed(C_WO);
      }
      bar_sync(5, 256);
      if (lane == 0) mbar_arrive(bars + 8 * B_P1DONE);
    }
    if (act) {
      {
        uint32_t wv[3];
#pragma unroll
        for (int q = 0; q < 3; q++) { int i = threadIdx.x + q * 256; wv[q] = i < 648 ? ldg_nc(reinterpret_cast<const uint32_t*>(p.wphi + p1_g * 1296) + i) : 0u; }
#pragma unroll
        for (int q = 0; q < 3; q++) { int i = threadIdx.x + q * 256; if (i < 720) sts128(sb + OFF_T + i * 16, 0u, 0u, 0u, 0u); }
        bar_sync(5, 256);
#pragma unroll
        for (int q = 0; q < 3; q++) {
          int i = threadIdx.x + q * 256;
          if (i < 648) {
            int c = i / 9, jn = i - c * 9, t = c / 18;
            uint32_t a = sb + OFF_T + (jn * 10 + (c >> 3)) * 128 + t * 32 + (c & 7) * 2;
            sts16(a, wv[q]); sts16(a + 16, wv[q] >> 16);
          }
        }
        fence_async_smem();
        bar_sync(5, 256);
      }
      float acc[108];
      zero_acc(acc);
      float ls0 = 0.f, ls1 = 0.f, lq0 = 0.f, lq1 = 0.f, lq2 = 0.f, lq3 = 0.f;
      const uint32_t aoff = (wg * 64 + wq * 16 + (lane & 15)) * 128, asw = (lane >> 4) ^ (lane & 7);
#pragma unroll 1
      for (int kb = 0; kb < 9; kb++) {
        const uint32_t st = sb + (kb & 3) * P1_STAGE;
        if (kb == 9 - SKEW1 && wg == 1) bar_sync(13, 256);
        mbar_wait(bars + 8 * (B_P1F + (kb & 3)), (kb >> 2) & 1);
        if (kb == 1 && threadIdx.x == 0) mbar_arrive(bars + 8 * B_GO);
        wg_fence();
        const uint64_t da = mkdesc(D_SW128, st + wg * 8192), dm = mkdesc(desc_hi(4096, 1024, 1), st + 16384), dr = mkdesc(desc_hi(128, 512, 0), st + 40960);
#pragma unroll
        for (int k = 0; k < 4; k++) {
          wgmma_ss<192, 0, 1, 0>(acc, da + 2 * k, dm + (k >> 1) * 768 + (k & 1) * 128, 1);
          wgmma_ss<24, 0, 1, 96>(acc, da + 2 * k, dr + (k >> 1) * 96 + (k & 1) * 16, 1);
        }
        wg_commit();
#pragma unroll
        for (int k = 0; k < 4; k++) {
          uint32_t a0, a1, a2, a3;
          ldsm_x4(st + aoff + ((asw ^ (2 * k)) << 4), a0, a1, a2, a3);
          float x0 = bf_lo(a0), x1 = bf_hi(a0), x2 = bf_lo(a2), x3 = bf_hi(a2);
          float y0 = bf_lo(a1), y1 = bf_hi(a1), y2 = bf_lo(a3), y3 = bf_hi(a3);
          ls0 += (x0 + x1) + (x2 + x3); ls1 += (y0 + y1) + (y2 + y3);
          lq0 = fmaf(x0, x0, lq0); lq2 = fmaf(x1, x1, lq2); lq0 = fmaf(x2, x2, lq0); lq2 = fmaf(x3, x3, lq2);
          lq1 = fmaf(y0, y0, lq1); lq3 = fmaf(y1, y1, lq3); lq1 = fmaf(y2, y2, lq1); lq3 = fmaf(y3, y3, lq3);
        }
        wg_wait<1>();
        if (kb > 0 && kb < 6 && tw < 2) mbar_arrive_remote(mapa(bars + 8 * (B_P1E + ((kb - 1) & 3)), tw));
      }
      if (wg == 0) bar_arrive(13, 256);
      const float mu0 = quad_sum(ls0) * (1.f / 576.f), mu1 = quad_sum(ls1) * (1.f / 576.f);
      const float rs0 = rsqrtf(fmaxf(quad_sum(lq0 + lq2) * (1.f / 576.f) - mu0 * mu0, 0.f) + 1e-5f);
      const float rs1 = rsqrtf(fmaxf(quad_sum(lq1 + lq3) * (1.f / 576.f) - mu1 * mu1, 0.f) + 1e-5f);
      mbar_wait(bars + 8 * B_CS, 0);
      const unsigned ep1 = *reinterpret_cast<const unsigned*>(smem + OFF_CS + 864);
      wg_wait<0>();
      reg_fence(acc);
      if (lane == 0) mbar_arrive(bars + 8 * B_P1DONE);
      const float2* csp = reinterpret_cast<const float2*>(smem + OFF_CS) + t4;
      const uint64_t dT = mkdesc(desc_hi(128, 1280, 0), sb + OFF_T);
      auto norm_pack = [&](int part, int j, uint32_t& lo, uint32_t& hi) {
        float2 c = csp[part * 36 + j * 4];
        int i = qkv_idx(part, j);
        if (part == 2) {
          lo = pack_bf16(fmaf(-mu0, c.x, acc[i]) * rs0, fmaf(-mu0, c.y, acc[i + 1]) * rs0);
          hi = pack_bf16(fmaf(-mu1, c.x, acc[i + 2]) * rs1, fmaf(-mu1, c.y, acc[i + 3]) * rs1);
        } else {
          lo = pack_bf16(fmaf(-mu0, c.x, acc[i]), fmaf(-mu0, c.y, acc[i + 1]));
          hi = pack_bf16(fmaf(-mu1, c.x, acc[i + 2]), fmaf(-mu1, c.y, acc[i + 3]));
        }
      };
      float pk[36], pq[36];
      const uint32_t pv = sb + OFF_PK + (wg ^ 1) * PV_BYTES;
      {
        uint32_t f[10][2];
#pragma unroll
        for (int j = 0; j < 9; j++) norm_pack(1, j, f[j][0], f[j][1]);
        f[9][0] = f[9][1] = 0u;
        wg_fence();
#pragma unroll
        for (int i = 0; i < 5; i++) wgmma_rs<72, 0, 0>(pk, f[2 * i][0], f[2 * i][1], f[2 * i + 1][0], f[2 * i + 1][1], dT + 16 * i, i != 0);
        wg_commit();
        if (wg == 1) mbar_wait(bars + 8 * B_P1DONE, 0);
        uint32_t v[9][2];
#pragma unroll
        for (int j = 0; j < 9; j++) norm_pack(2, j, v[j][0], v[j][1]);
        const uint32_t va = pv + PV_V + (wq * 16 + (lane & 15)) * 16 + (lane >> 4) * 1024;
        const uint32_t one = t4 == 0 ? 0x00003F80u : 0u;
        stsm_x4(va, v[0][0], v[0][1], v[1][0], v[1][1]);
        stsm_x4(va + 2 * 1024, v[2][0], v[2][1], v[3][0], v[3][1]);
        stsm_x4(va + 4 * 1024, v[4][0], v[4][1], one, one);
        stsm_x4(va + 6 * 1024, v[5][0], v[5][1], v[6][0], v[6][1]);
        stsm_x4(va + 8 * 1024, v[7][0], v[7][1], v[8][0], v[8][1]);
        wg_wait<0>();
        reg_fence(pk);
      }
      {
        uint32_t o[18];
        uint32_t a = pv + (wq * 16 + r8) * 16 + t4 * 5 * PK_CS;
        featmap<0>(pk, rs0, o);
        sts128(a, o[0], o[1], o[2], o[3]); sts128(a + PK_CS, o[4], o[5], o[6], o[7]);
        sts128(a + 2 * PK_CS, o[8], o[9], o[10], o[11]); sts128(a + 3 * PK_CS, o[12], o[13], o[14], o[15]);
        sts64(a + 4 * PK_CS, o[16], o[17]);
        a += 128;
        featmap<2>(pk, rs1, o);
        sts128(a, o[0], o[1], o[2], o[3]); sts128(a + PK_CS, o[4], o[5], o[6], o[7]);
        sts128(a + 2 * PK_CS, o[8], o[9], o[10], o[11]); sts128(a + 3 * PK_CS, o[12], o[13], o[14], o[15]);
        sts64(a + 4 * PK_CS, o[16], o[17]);
      }
      fence_async_smem();
      if (wg == 0) bar_sync(1, 128); else bar_sync(5, 256);
      uint32_t fqa[10][2];
      {
        float c[40];
        wg_fence();
        const uint64_t da = mkdesc(desc_hi(128, 1024, 0), sb + OFF_PK + PV_V + wg * 2048), db = mkdesc(desc_hi(128, PK_CS, 0), sb + OFF_PK + wg * 10 * PK_CS);
#pragma unroll
        for (int ks = 0; ks < 4; ks++) wgmma_ss<80, 1, 1, 0>(c, da + PV_BYTES / 16 + ks * 16, db + PV_BYTES / 16 + ks * 16, ks != 0);
        if (wg == 0) bar_sync(5, 256);
#pragma unroll
        for (int ks = 0; ks < 4; ks++) wgmma_ss<80, 1, 1, 0>(c, da + ks * 16, db + ks * 16, 1);
        wg_commit();
#pragma unroll
        for (int j = 0; j < 9; j++) { norm_pack(0, j, fqa[j][0], fqa[j][1]); asm volatile("" : "+r"(fqa[j][0]), "+r"(fqa[j][1])::"memory"); }
        fqa[9][0] = fqa[9][1] = 0u;
        wg_wait<0>();
        reg_fence(c);
        bar_sync(5, 256);
#pragma unroll
        for (int hh = 0; hh < 2; hh++) {
          const int pos = 2 * wg + 2 * wq + hh;
          const int col = (pos < 5 ? 8 * pos : 8 * pos - 8) + r8;
#pragma unroll
          for (int hl = 0; hl < 2; hl++) {
            const int head = 2 * wg + hl;
            const int d = pos == 5 ? 18 + r8 : col - 18 * head;
            if (d >= 0 && d < (pos == 5 ? 19 : 18)) {
              const uint32_t a = sb + OFF_KVS + head * 3680 + d * 192;
#pragma unroll
              for (int i = 0; i < 5; i++) {
                const int pr = 4 * i + t4;
                if (i < 4 || t4 < 2) sts64(a + (pr + ((pr * 11) >> 5)) * 8, __float_as_uint(c[20 * hl + 4 * i + 2 * hh]), __float_as_uint(c[20 * hl + 4 * i + 2 * hh + 1]));
              }
            }
          }
        }
#pragma unroll
        for (int q = 0; q < 2; q++) { const int i = threadIdx.x + q * 256; if (i < 460) sts64(sb + OFF_KVS + i * 32 + 24, 0x3f800000u, 0u); }
      }
      fence_async_smem();
      bar_arrive(3, 256 + 32);
      uint32_t fq0[18], fq1[18];
      {
        wg_fence();
#pragma unroll
        for (int i = 0; i < 5; i++) wgmma_rs<72, 0, 0>(pq, fqa[2 * i][0], fqa[2 * i][1], fqa[2 * i + 1][0], fqa[2 * i + 1][1], dT + 16 * i, i != 0);
        wg_commit();
        wg_wait<0>();
        reg_fence(pq);
        if (lane == 0) mbar_arrive(bars + 8 * B_TFREE);
        featmap<0>(pq, rs0, fq0);
        featmap<2>(pq, rs1, fq1);
      }
      mbar_wait(bars + 8 * B_X, 0);
      uint32_t xr[20];
      {
        const uint32_t xa = sb + OFF_X + (wq * 16 + (lane & 15)) * 288 + (wg * 9 + (lane >> 4)) * 16;
#pragma unroll
        for (int j = 0; j < 10; j += 2) ldsm_x4(xa + j * 16, xr[2 * j], xr[2 * j + 1], xr[2 * j + 2], xr[2 * j + 3]);
      }
#pragma unroll 1
      for (int tr = 0; tr < 100000; tr++) {
        mbar_wait(bars + 8 * B_KVL, tr & 1);
        const int r = lane & 7, t = r >> 1;
        uint32_t bad = 0;
#pragma unroll
        for (int q = 0; q < 2; q++) {
          const int c = (threadIdx.x >> 3) + q * 32, jn = c / 6, d = 2 * jn + (r & 1);
          if (c < 60) {
            float4 v0 = make_float4(0.f, 0.f, 0.f, 0.f), v1 = make_float4(0.f, 0.f, 16.f, 0.f);
            if (d < 19) {
              const float4* src = reinterpret_cast<const float4*>(smem + OFF_KVS + t * 3680 + d * 192 + (c - jn * 6) * 32);
              v0 = src[0]; v1 = src[1];
            }
            bad |= v1.z != 16.f;
            const uint32_t w[3] = {pack_bf16(v0.x, v0.y), pack_bf16(v0.z, v0.w), pack_bf16(v1.x, v1.y)};
#pragma unroll
            for (int i = 0; i < 3; i++)
              sts128(sb + OFF_KVB + c * 384 + i * 128 + r * 16, t == 0 ? w[i] : 0u, t == 1 ? w[i] : 0u, t == 2 ? w[i] : 0u, t == 3 ? w[i] : 0u);
          }
        }
        fence_async_smem();
        asm volatile("{\n.reg .pred p;\nsetp.ne.u32 p, %0, 0;\nbar.red.or.pred p, 5, 256, p;\nselp.u32 %0, 1, 0, p;\n}" : "+r"(bad)::"memory");
        if (!bad) break;
        if (threadIdx.x == 0) {
          mbar_expect_tx(bars + 8 * B_KVL, KV_BYTES);
          bulk_load(sb + OFF_KVS, g_kv + p1_g * KV_BYTES, KV_BYTES, bars + 8 * B_KVL);
        }
      }
      {
        float oa[40];
        if (wg == 1) bar_sync(6, 256);
        wg_fence();
        const uint64_t dk = mkdesc(desc_hi(128, 18 * 128, 0), sb + OFF_KVB);
#pragma unroll
        for (int i = 0; i < 9; i++) wgmma_rs<80, 0, 0>(oa, fq0[2 * i], fq1[2 * i], fq0[2 * i + 1], fq1[2 * i + 1], dk + i * 16, i != 0);
        wg_commit();
        if (wg == 0) bar_arrive(6, 256);
        wg_wait<0>();
        reg_fence(oa);
        const float rd0 = rcp(oa[36] + 1e-6f), rd1 = rcp(oa[38] + 1e-6f);
        uint32_t* og = reinterpret_cast<uint32_t*>(g_o + ((size_t)(p1_r * 2 + wg) * 72 + p1_g * 9) * 1024 + wq * 256) + lane;
#pragma unroll
        for (int j = 0; j < 9; j++) {
          og[j * 256] = pack_bf16(oa[4 * j] * rd0, oa[4 * j + 1] * rd0);
          og[j * 256 + 32] = pack_bf16(oa[4 * j + 2] * rd1, oa[4 * j + 3] * rd1);
        }
      }
      bar_sync(1 + wg, 128);
      if (tw == 0) {
        mbar_arrive(bars + 8 * B_P2DONE);
        publish_fence();
        asm volatile("st.relaxed.gpu.global.u32 [%0], %1;" ::"l"(&g_cnt[(C_O + p1_r * 2 + wg) * 32 + p1_g]), "r"(ep1) : "memory");
      }
      float ha[36], pv0 = 0.f, pv1 = 0.f;
#pragma unroll
      for (int j = 0; j < 9; j++) {
        ha[4 * j] = bf_lo(xr[2 * j]); ha[4 * j + 1] = bf_hi(xr[2 * j]); ha[4 * j + 2] = bf_lo(xr[2 * j + 1]); ha[4 * j + 3] = bf_hi(xr[2 * j + 1]);
        pv0 += ha[4 * j] + ha[4 * j + 1]; pv1 += ha[4 * j + 2] + ha[4 * j + 3];
      }
      pv0 = quad_sum(pv0) * (1.f / 72.f); pv1 = quad_sum(pv1) * (1.f / 72.f);
#pragma unroll
      for (int i = 0; i < 36; i++) ha[i] -= (i & 2) ? pv1 : pv0;
      mbar_wait(bars + 8 * B_WO, 0);
#pragma unroll 1
      for (int kb = 0; kb < 9; kb++) {
        mbar_wait(bars + 8 * (B_OF + kb), 0);
        wg_fence();
        const uint64_t da = mkdesc(desc_hi(1024, 128, 0), sb + (kb < 7 ? OFF_O + kb * 8192 : (kb - 7) * 8192));
        const uint64_t db = mkdesc(desc_hi(2304, 128, 0), sb + kb * 18432 + wg * 1152);
#pragma unroll
        for (int k = 0; k < 4; k++) wgmma_ss<72, 0, 0, 0>(ha, da + 128 * k, db + 288 * k, 1);
        wg_commit();
        if (kb >= 2 && !(kb & 1)) { wg_wait<1>(); if (tw == 0) mbar_arrive(bars + 8 * (B_P3K - 1) + 4 * kb); }
      }
      wg_wait<0>();
      reg_fence(ha);
      float s0 = 0.f, s1 = 0.f, q0 = 0.f, q1 = 0.f, q2 = 0.f, q3 = 0.f;
#pragma unroll
      for (int j = 0; j < 9; j++) {
        s0 += ha[4 * j] + ha[4 * j + 1]; s1 += ha[4 * j + 2] + ha[4 * j + 3];
        q0 = fmaf(ha[4 * j], ha[4 * j], q0); q2 = fmaf(ha[4 * j + 1], ha[4 * j + 1], q2);
        q1 = fmaf(ha[4 * j + 2], ha[4 * j + 2], q1); q3 = fmaf(ha[4 * j + 3], ha[4 * j + 3], q3);
      }
      s0 = quad_sum(s0) * (1.f / 72.f); s1 = quad_sum(s1) * (1.f / 72.f);
      q0 = fmaxf(fmaf(-72.f * s0, s0, quad_sum(q0 + q2)), 0.f); q1 = fmaxf(fmaf(-72.f * s1, s1, quad_sum(q1 + q3)), 0.f);
      const float m0 = pv0 + s0, m1 = pv1 + s1;
      if (t4 < 2) sts64(sb + OFF_LN + (wq * 16 + r8 + t4 * 8) * 16 + wg * 8, __float_as_uint(t4 ? m1 : m0), __float_as_uint(t4 ? q1 : q0));
      bar_sync(5, 256);
      if (threadIdx.x < 64) {
        const float4 e = *reinterpret_cast<const float4*>(smem + OFF_LN + threadIdx.x * 16);
        const float dm = e.x - e.z;
        st_relaxed_v4(g_mb + L * 72 + threadIdx.x, __float_as_uint(0.5f * (e.x + e.z)), __float_as_uint(e.y + e.w + 36.f * dm * dm), 0u, ~ep1);
      }
      {
        uint4 e; int it = 0;
        const uint4* mb = g_mb + ((L & 0x79) + (threadIdx.x >> 6) * 2) * 72 + (threadIdx.x & 63);
        do { e = ld_relaxed_v4(mb); } while (e.w != ~ep1 && ++it < 2000000);
        sts64(sb + OFF_E + 18432 + (threadIdx.x & 63) * 32 + (threadIdx.x >> 6) * 8, e.x, e.y);
      }
      bar_sync(5, 256);
      float mean[2], scale[2];
#pragma unroll
      for (int hr = 0; hr < 2; hr++) {
        const float4* sp = reinterpret_cast<const float4*>(smem + OFF_E + 18432 + (wq * 16 + r8 + hr * 8) * 32);
        const float4 a = sp[0], b = sp[1];
        const float mu = 0.25f * ((a.x + a.z) + (b.x + b.z));
        const float d0 = a.x - mu, d1 = a.z - mu, d2 = b.x - mu, d3 = b.z - mu;
        const float var = ((a.y + a.w) + (b.y + b.w) + 144.f * (d0 * d0 + d1 * d1 + d2 * d2 + d3 * d3)) * (1.f / 576.f);
        scale[hr] = 0.5f * rsqrtf(fmaf(1e-5f, var + 1e-5f, var));
        mean[hr] = ((hr ? pv1 : pv0) - mu) * scale[hr];
      }
      {
        uint32_t* hg = reinterpret_cast<uint32_t*>(g_hn + ((size_t)p3_b * 72 + p3_db * 18 + wg * 9) * 1024 + wq * 256) + lane;
#pragma unroll
        for (int j = 0; j < 9; j++) {
          hg[j * 256] = pack_bf16(fmaf(ha[4 * j], scale[0], mean[0]), fmaf(ha[4 * j + 1], scale[0], mean[0]));
          hg[j * 256 + 32] = pack_bf16(fmaf(ha[4 * j + 2], scale[1], mean[1]), fmaf(ha[4 * j + 3], scale[1], mean[1]));
        }
      }
      bar_sync(5, 256);
      if (threadIdx.x == 0) {
        mbar_arrive(bars + 8 * B_P3DONE);
        publish_fence();
        if (p3_b < 6 && !rank) signal_relaxed(C_HF);
        signal_relaxed(C_H);
      }
      {
        uint32_t hw[18];
#pragma unroll
        for (int j = 0; j < 9; j++) { hw[j] = pack_bf16(ha[4 * j] + pv0, ha[4 * j + 1] + pv0); hw[9 + j] = pack_bf16(ha[4 * j + 2] + pv1, ha[4 * j + 3] + pv1); }
        const uint32_t hb = sb + OFF_H + wg * 4608;
#pragma unroll
        for (int hr = 0; hr < 2; hr++) {
          sts128(hb + hr * 9216 + tw * 16, hw[9 * hr], hw[9 * hr + 1], hw[9 * hr + 2], hw[9 * hr + 3]);
          sts128(hb + hr * 9216 + 2048 + tw * 16, hw[9 * hr + 4], hw[9 * hr + 5], hw[9 * hr + 6], hw[9 * hr + 7]);
          sts32f(hb + hr * 9216 + 4096 + tw * 4, __uint_as_float(hw[9 * hr + 8]));
        }
      }
    }
    int s = 0, ph = 0;
    const int brow = (act ? p5_sb : 0) * 128 + wg * 64 + wq * 16 + r8;
    const float b0 = bf_lo(ldg_nc_u16(p.b2 + brow)), b1 = bf_lo(ldg_nc_u16(p.b2 + brow + 8));
    {
      const int f = (p4_fb + wg) * 64 + wq * 16 + r8;
      const float bb0 = 0.5f * __bfloat162float(p.b1[f]), bb1 = 0.5f * __bfloat162float(p.b1[f + 8]);
      int prev = 0;
#define P4_LOOP(NKB, BODY)                                                                     \
  _Pragma("unroll 1") for (int kb = 0; kb < NKB; kb++) {                                       \
    mbar_wait(bars + 8 * (B_RF + s), ph);                                                      \
    wg_fence();                                                                                \
    const uint64_t da = mkdesc(D_SW128, sb + slot(s) + wg * 8192);                             \
    _Pragma("unroll") for (int k = 0; k < 4; k++) { BODY }                                     \
    wg_commit();                                                                               \
    if (kb > 0) { wg_wait<1>(); if (tw == 0) mbar_arrive(bars + 8 * (B_RE + prev)); }          \
    prev = s;                                                                                  \
    if (++s == NST) { s = 0; ph ^= 1; }                                                        \
  }
      uint32_t* ug = reinterpret_cast<uint32_t*>(g_u + ((size_t)(p4_fb + wg) * 576 + p4_d0) * 128 + wq * 256) + lane;
      if (p4_main) {
        float t[80];
#pragma unroll
        for (int i = 0; i < 80; i++) t[i] = (i & 2) ? bb1 : bb0;
        P4_LOOP(32, if (k == 0 && kb == 32 - SKEW4 && wg == 1) bar_sync(12, 256);
                    (wgmma_ss<160, 1, 1, 0>(t, da + 128 * k, mkdesc(D_NCORE, sb + slot(s) + 16384) + 16 * k, 1));)
        const bool urgent = p4_fg % 6 == 0 && p4_j < 6;
        if (wg == 0 && !urgent) bar_arrive(12, 256);
        wg_wait<0>();
        reg_fence(t);
        if (tw == 0) mbar_arrive(bars + 8 * (B_RE + prev));
#pragma unroll
        for (int j = 0; j < 20; j++) {
          ug[j * 256] = pack_bf16(gelu(t[4 * j]), gelu(t[4 * j + 1]));
          ug[j * 256 + 32] = pack_bf16(gelu(t[4 * j + 2]), gelu(t[4 * j + 3]));
        }
        if (wg == 0 && urgent) bar_arrive(12, 256);
      } else {
        float x[48], y[48];
        if (wg == 0) {
          const float bc0 = 0.5f * __bfloat162float(p.b1[f + 128]), bc1 = 0.5f * __bfloat162float(p.b1[f + 136]);
          float t[48], u[48];
          zero_acc(t); zero_acc(u);
          P4_LOOP(32, (wgmma_ss<96, 1, 1, 0>(t, da + 128 * k, mkdesc(D_NCORE, sb + slot(s) + 24576) + 16 * k, 1));
                      (wgmma_ss<96, 1, 1, 0>(u, da + 1024 + 128 * k, mkdesc(D_NCORE, sb + slot(s) + 24576) + 16 * k, 1));)
          wg_wait<0>();
          reg_fence(t); reg_fence(u);
#pragma unroll
          for (int i = 0; i < 48; i++) { x[i] = t[i] + ((i & 2) ? bb1 : bb0); y[i] = u[i] + ((i & 2) ? bc1 : bc0); }
        } else {
          float t[48];
          zero_acc(t);
          P4_LOOP(32, (wgmma_ss<96, 1, 1, 0>(t, da + 128 * k, mkdesc(D_NCORE, sb + slot(s) + 24576) + 16 * k, 1));)
          wg_wait<0>();
          reg_fence(t);
#pragma unroll
          for (int i = 0; i < 48; i++) { x[i] = t[i] + ((i & 2) ? bb1 : bb0); y[i] = 0.f; }
        }
        if (tw == 0) mbar_arrive(bars + 8 * (B_RE + prev));
#pragma unroll 1
        for (int c = 0; c < 2 - wg; c++) {
#pragma unroll
          for (int j = 0; j < 12; j++) {
            ug[c * 36864 + j * 256] = pack_bf16(gelu(x[4 * j]), gelu(x[4 * j + 1]));
            ug[c * 36864 + j * 256 + 32] = pack_bf16(gelu(x[4 * j + 2]), gelu(x[4 * j + 3]));
          }
#pragma unroll
          for (int i = 0; i < 48; i++) x[i] = y[i];
        }
      }
      bar_arrive(14 + wg, 128 + 32);
    }
    if (act) {
      const bool fin = wg == rank;
      const int srow = p5_sb * 128 + wg * 64 + wq * 16;
      float acc[72];
      {
        const uint8_t* hp = smem + OFF_H;
        const uint32_t keep = fin ? ~0u : 0u;
        const float c0 = fin ? b0 : 0.f, c1 = fin ? b1 : 0.f;
#pragma unroll
        for (int i = 0; i < 4; i++) {
          const uint4 ha = reinterpret_cast<const uint4*>(hp + i * 4608)[tw], hb = reinterpret_cast<const uint4*>(hp + i * 4608 + 2048)[tw];
          const uint32_t w[9] = {ha.x, ha.y, ha.z, ha.w, hb.x, hb.y, hb.z, hb.w, reinterpret_cast<const uint32_t*>(hp + i * 4608 + 4096)[tw]};
#pragma unroll
          for (int j = 0; j < 9; j++) {
            acc[36 * (i & 1) + 4 * j + (i & 2)] = bf_lo(w[j] & keep) + ((i & 2) ? c1 : c0);
            acc[36 * (i & 1) + 4 * j + (i & 2) + 1] = bf_hi(w[j] & keep) + ((i & 2) ? c1 : c0);
          }
        }
      }
      int prev = 0;
#pragma unroll 1
      for (int kb = 0; kb < 36; kb++) {
        if (kb == 36 - SKEW5 && fin) bar_sync(11, 256);
        mbar_wait(bars + 8 * (B_RF + s), ph);
        wg_fence();
        const uint64_t da = mkdesc(D_SW128, sb + slot(s) + wg * 8192), db = mkdesc(D_NCORE, sb + slot(s) + 16384);
#pragma unroll
        for (int k = 0; k < 4; k++) wgmma_ss<144, 1, 1, 0>(acc, da + 128 * k, db + 16 * k, 1);
        wg_commit();
        if (kb > 0) { wg_wait<1>(); if (tw == 0) mbar_arrive(bars + 8 * (B_RE + prev)); }
        prev = s;
        if (++s == NST) { s = 0; ph ^= 1; }
      }
      if (!fin) bar_arrive(11, 256);
      wg_wait<0>();
      reg_fence(acc);
      const uint32_t rbuf = sb + OFF_E + wq * 4608, rbar = bars + 8 * (B_RED + wq);
      if (!fin) {
        bar_sync(1 + wg, 128);
        const uint32_t s0 = sb + wq * STAGE + wg * 8192;
#pragma unroll
        for (int q = 0; q < 9; q++)
          sts128(s0 + q * 512 + lane * 16, pack_bf16(acc[8 * q], acc[8 * q + 1]), pack_bf16(acc[8 * q + 2], acc[8 * q + 3]),
                 pack_bf16(acc[8 * q + 4], acc[8 * q + 5]), pack_bf16(acc[8 * q + 6], acc[8 * q + 7]));
        fence_async_smem();
        mbar_wait(bars + 8 * B_EFREE, 0);
        __syncwarp();
        if (elect_one())
          asm volatile("cp.async.bulk.shared::cluster.shared::cta.mbarrier::complete_tx::bytes [%0], [%1], %2, [%3];"
                       ::"r"(mapa(rbuf, rank ^ 1)), "r"(s0), "r"(4608), "r"(mapa(rbar, rank ^ 1)) : "memory");
        mbar_wait(bars + 8 * B_ACK, 0);
        __syncwarp();
      } else {
        mbar_wait(rbar, 0);
        if (lane == 0) mbar_arrive_remote(mapa(bars + 8 * B_ACK, rank ^ 1));
        const uint32_t oa = rbuf - 18432 + (lane & 15) * 288 + (lane >> 4) * 16;
#pragma unroll
        for (int q = 0; q < 9; q++) {
          const uint4 r = *reinterpret_cast<const uint4*>(smem + OFF_E + wq * 4608 + q * 512 + lane * 16);
          stsm_x4(oa + q * 32, pack_bf16(acc[8 * q] + bf_lo(r.x), acc[8 * q + 1] + bf_hi(r.x)), pack_bf16(acc[8 * q + 2] + bf_lo(r.y), acc[8 * q + 3] + bf_hi(r.y)),
                  pack_bf16(acc[8 * q + 4] + bf_lo(r.z), acc[8 * q + 5] + bf_hi(r.z)), pack_bf16(acc[8 * q + 6] + bf_lo(r.w), acc[8 * q + 7] + bf_hi(r.w)));
        }
        fence_async_smem();
        __syncwarp();
        if (elect_one()) {
          asm volatile("cp.async.bulk.tensor.2d.global.shared::cta.bulk_group [%0, {%2, %3}], [%1];" ::"l"(&mOut), "r"(rbuf - 18432), "r"(p5_db * 144), "r"(srow) : "memory");
          bulk_commit_wait_read();
        }
      }
    } else {
      mbar_wait(bars + 8 * B_EFREE, 0);
    }
  }
}

typedef CUresult (*EncodeFn)(CUtensorMap*, CUtensorMapDataType, cuuint32_t, void*, const cuuint64_t*, const cuuint64_t*,
                             const cuuint32_t*, const cuuint32_t*, CUtensorMapInterleave, CUtensorMapSwizzle,
                             CUtensorMapL2promotion, CUtensorMapFloatOOBfill);

CUtensorMap make_map(EncodeFn enc, const void* ptr, int rank, const cuuint64_t* dims, const cuuint64_t* strides, const cuuint32_t* box,
                     CUtensorMapSwizzle sw, CUtensorMapL2promotion promo = CU_TENSOR_MAP_L2_PROMOTION_L2_128B) {
  CUtensorMap m;
  cuuint32_t es[3] = {1, 1, 1};
  enc(&m, CU_TENSOR_MAP_DATA_TYPE_BFLOAT16, rank, const_cast<void*>(ptr), dims, strides, box, es, CU_TENSOR_MAP_INTERLEAVE_NONE,
      sw, promo, CU_TENSOR_MAP_FLOAT_OOB_FILL_NONE);
  return m;
}
CUtensorMap make_wmap(EncodeFn enc, const void* ptr, uint64_t rows, uint64_t cols, uint32_t nblk) {
  cuuint64_t dims[3] = {64, rows, cols / 64};
  cuuint64_t strides[2] = {cols * 2, 128};
  cuuint32_t box[3] = {64, 64, nblk};
  return make_map(enc, ptr, 3, dims, strides, box, CU_TENSOR_MAP_SWIZZLE_128B, CU_TENSOR_MAP_L2_PROMOTION_L2_256B);
}

}

extern "C" void kernel_launch(void* const* d_in, const int* in_sizes, int n_in, void* d_out, int out_size) {
  static EncodeFn enc = nullptr;
  if (!enc) {
    cudaDriverEntryPointQueryResult qr;
    cudaGetDriverEntryPoint("cuTensorMapEncodeTiled", (void**)&enc, cudaEnableDefault, &qr);
    cudaFuncSetAttribute(fused_kernel, cudaFuncAttributeMaxDynamicSharedMemorySize, SMEM_BYTES);
  }
  Params p;
  p.wqkv = (const __nv_bfloat16*)d_in[1];
  p.wphi = (const __nv_bfloat16*)d_in[2];
  p.b1 = (const __nv_bfloat16*)d_in[6];
  p.b2 = (const __nv_bfloat16*)d_in[8];
  CUtensorMap mX, mXr, mWm, mWr;
  {
    cuuint64_t dims[2] = {576, 2048}; cuuint64_t strides[1] = {1152}; cuuint32_t box[2] = {64, 128};
    mX = make_map(enc, d_in[0], 2, dims, strides, box, CU_TENSOR_MAP_SWIZZLE_128B);
    cuuint32_t boxr[2] = {144, 64};
    mXr = make_map(enc, d_in[0], 2, dims, strides, boxr, CU_TENSOR_MAP_SWIZZLE_NONE);
  }
  {
    cuuint64_t dims[3] = {576, 576, 3}; cuuint64_t strides[2] = {3456, 1152};
    cuuint32_t boxm[3] = {64, 32, 3}, boxr[3] = {8, 32, 3};
    mWm = make_map(enc, d_in[1], 3, dims, strides, boxm, CU_TENSOR_MAP_SWIZZLE_128B);
    mWr = make_map(enc, d_in[1], 3, dims, strides, boxr, CU_TENSOR_MAP_SWIZZLE_NONE);
  }
  CUtensorMap mWo, mOut;
  {
    cuuint64_t dims[2] = {576, 2048}; cuuint64_t strides[1] = {1152}; cuuint32_t box[2] = {144, 16};
    mOut = make_map(enc, d_out, 2, dims, strides, box, CU_TENSOR_MAP_SWIZZLE_NONE);
  }
  {
    cuuint64_t dims[2] = {576, 576}; cuuint64_t strides[1] = {1152}; cuuint32_t box[2] = {72, 72};
    mWo = make_map(enc, d_in[3], 2, dims, strides, box, CU_TENSOR_MAP_SWIZZLE_NONE);
  }
  CUtensorMap mW1a = make_wmap(enc, d_in[5], 2048, 4608, 2);
  CUtensorMap mW1b = make_wmap(enc, d_in[5], 2048, 4608, 3);
  CUtensorMap mW2 = make_wmap(enc, d_in[7], 4608, 2048, 2);
  fused_kernel<<<NCTA, NTHREADS, SMEM_BYTES, cudaStreamPerThread>>>(mX, mWm, mWr, mXr, mWo, mW1a, mW1b, mW2, mOut, p);
}
```
